```python
import torch

def _softmax(x, axis=-1):
    return torch.softmax(x, dim=axis)
def _gelu(x):
    return torch.nn.functional.gelu(x, approximate="tanh")
def _silu(x):
    return torch.nn.functional.silu(x)
def _sigmoid(x):
    return torch.sigmoid(x)
def _layernorm(x, axis=-1, eps=1e-5):
    m = x.mean(dim=axis, keepdim=True)
    v = x.var(dim=axis, keepdim=True, unbiased=False)
    return (x - m) / torch.sqrt(v + eps)
def _scatter_add(tgt, idx, src, axis=0):
    return tgt.clone().index_add_(axis, idx, src)
def _segment_sum(src, seg, n):
    out = torch.zeros((n,) + src.shape[1:], dtype=src.dtype)
    return out.index_add_(0, seg, src)
def _pad(x, pw):
    flat = tuple(v for pair in reversed(pw) for v in pair)
    return torch.nn.functional.pad(x, flat)

kernel_name = 'sequential_preLN__mha_block_cached__swiglu_ffn__decode'

def setup_inputs():

    _w = (lambda a: (lambda t: t.to(torch.bfloat16) if t.is_floating_point() else t)(torch.as_tensor(a)))
    def _A_setup():
        B, Sq, D = 1, 1, 640
        H, Sk, Dh = 32, 32768, 192
        return {
            "x": _w((lambda *s: torch.randn(*s, dtype=torch.bfloat16) * 0.05)(B, Sq, D)),
            "k_cache": _w((lambda *s: torch.randn(*s, dtype=torch.bfloat16) * 3.2)(B, H, Sk, Dh)),
            "v_cache": _w((lambda *s: torch.randn(*s, dtype=torch.bfloat16) * 0.4)(B, H, Sk, Dh)),
            "wq": _w((lambda *s: torch.randn(*s, dtype=torch.bfloat16) * 3.2)(D, H * Dh) * (D ** -0.5)),
            "wo": _w((lambda *s: torch.randn(*s, dtype=torch.bfloat16) * 0.4)(H * Dh, D) * ((H * Dh) ** -0.5)),
        }
    _A_in = _A_setup()

    def _B_setup():
        B, S, D, F = 1, 1, 640, 1536
        return {
            "x": _w((lambda *s: torch.randn(*s, dtype=torch.bfloat16) * 0.05)(B, S, D)),
            "w_gate": _w((lambda *s: torch.randn(*s, dtype=torch.bfloat16) * 0.05)(D, F)),
            "w_up": _w((lambda *s: torch.randn(*s, dtype=torch.bfloat16) * 0.05)(D, F)),
            "w_down": _w((lambda *s: torch.randn(*s, dtype=torch.bfloat16) * 0.05)(F, D)),
        }
    _B_in = _B_setup()

    return {
        "A_x": _A_in["x"],
        "A_k_cache": _A_in["k_cache"],
        "A_v_cache": _A_in["v_cache"],
        "A_wq": _A_in["wq"],
        "A_wo": _A_in["wo"],
        "B_x": _B_in["x"],
        "B_w_gate": _B_in["w_gate"],
        "B_w_up": _B_in["w_up"],
        "B_w_down": _B_in["w_down"],
    }

def reference(A_x, A_k_cache, A_v_cache, A_wq, A_wo, B_x, B_w_gate, B_w_up, B_w_down):
    def _A_ref(x, k_cache, v_cache, wq, wo):
        B, Sq, D = x.shape
        H, Dh = 32, 192
        q = (lambda x, *d: x.permute(*d))((x @ wq).reshape(B, Sq, H, Dh), 0, 2, 1, 3)
        scores = torch.einsum("bhqd,bhkd->bhqk", q, k_cache) * (Dh ** -0.5)
        p = _softmax(scores, axis=-1)
        o = torch.einsum("bhqk,bhkd->bhqd", p, v_cache)
        return (lambda x, *d: x.permute(*d))(o, 0, 2, 1, 3).reshape(B, Sq, H * Dh) @ wo

    def _B_ref(x, w_gate, w_up, w_down):
        g = _silu(x @ w_gate)
        u = x @ w_up
        return (g * u) @ w_down

    x = A_x
    h = x + _A_ref(_layernorm(x, axis=-1), A_k_cache, A_v_cache, A_wq, A_wo)
    h2 = h + _B_ref(_layernorm(h, axis=-1), B_w_gate, B_w_up, B_w_down)
    return h2
```

```cpp
#include <cuda_runtime.h>
#include <cuda.h>
#include <cuda_bf16.h>
#include <stdint.h>

namespace fused {

constexpr int DM = 640;
constexpr int NH = 32;
constexpr int SK = 32768;
constexpr int DH = 192;
constexpr int HD = NH * DH;
constexpr int FF = 1536;
constexpr int ROWB = DH * 2;
constexpr int ITEM_KEYS = 64;
constexpr int CHUNK = ITEM_KEYS * ROWB;
constexpr int ITEMS_PER_HEAD = SK / ITEM_KEYS;
constexpr int NITEMS = NH * ITEMS_PER_HEAD;
constexpr int NSLOT = 6;
constexpr int NPRE = NSLOT / 2;
constexpr int NCOMB = 4;
constexpr int MAXS = 128;
constexpr int NGU = FF / 16;
constexpr int NDN = DM / 8;
#define START_W 2
#define NPF 0
#define NDRY 1
constexpr int NQS = HD / 48;
constexpr int WQ_BOX_ROWS = 160;
constexpr int NTHREADS = 320;

constexpr int SM_RING = 0;
constexpr int SM_WG = NSLOT * CHUNK;
constexpr int SM_WU = SM_WG + DM * 32;
constexpr int SM_WD = SM_WU + DM * 32;
constexpr int SM_Q = SM_WD + FF * 16;
constexpr int SM_OBUF = SM_Q + HD * 2;
constexpr int SM_ML = SM_OBUF + 2 * 4 * DH * 4;
constexpr int SM_BAR = SM_ML + 160;
constexpr int SM_META = SM_BAR + 16 * 8;
constexpr int SM_TAG = SM_META + 16;
constexpr int SM_CS = SM_TAG + 16;
constexpr int SM_TOTAL = SM_CS + 128;
constexpr int SM_XS = SM_Q;
constexpr int SM_XN = SM_Q + DM * 4;
constexpr int SM_QRED = SM_XN + DM * 2;
constexpr int SM_WQ = SM_WG;
constexpr int SM_H = 0;
constexpr int SM_RED = DM * 4;
constexpr int SM_RED2 = SM_RED + 8 * 32 * 4;
constexpr int SM_ST = SM_RED2 + 8 * 8 * 4;
constexpr int WO_PITCH = DM * 2 + 16;
constexpr int WO_BUF = 48 * WO_PITCH;
constexpr int NWO = 3;
constexpr int SC_OB = NWO * WO_BUF;
constexpr int SC_ML = SC_OB + 2 * 8 * 48 * 4;
static_assert(SC_ML + 128 <= SM_BAR, "combine smem overlaps barriers");
static_assert(SM_TOTAL <= 232448, "smem");

constexpr float LOG2E = 1.4426950408889634f;
constexpr float QK_SCALE = 0.07216878364870322f;
constexpr float NEG_INF = -__builtin_huge_valf();

__device__ unsigned int g_epoch;
__device__ unsigned int g_work;
__device__ unsigned int g_exit;
__device__ uint4 g_q[HD / 6];
__device__ uint4 g_phdr[NH][MAXS];
__device__ uint4 g_pdat[NH][NCOMB][MAXS][16];
__device__ uint4 g_attn[NCOMB][8][32];
__device__ uint4 g_act[NGU][4];
__device__ unsigned int g_bell[32][32];
__device__ uint4 g_dummy[64];

__device__ __forceinline__ uint32_t s2u(const void* p) { return (uint32_t)__cvta_generic_to_shared(p); }
__device__ __forceinline__ uint32_t pack_bf2(float lo, float hi) {
    uint32_t r;
    asm("cvt.rn.bf16x2.f32 %0, %1, %2;" : "=r"(r) : "f"(hi), "f"(lo));
    return r;
}
__device__ __forceinline__ float bfr(float x) { return __uint_as_float(pack_bf2(0.f, x)); }
template <typename T>
__device__ __forceinline__ T* opaque(T* p) {
    asm volatile("" : "+l"(p));
    return p;
}
__device__ __forceinline__ uint32_t opaque(uint32_t v) {
    asm volatile("" : "+r"(v));
    return v;
}
__device__ __forceinline__ float4 lds128(uint32_t a) {
    float4 v;
    asm volatile("ld.shared.v4.f32 {%0,%1,%2,%3}, [%4];" : "=f"(v.x), "=f"(v.y), "=f"(v.z), "=f"(v.w) : "r"(a) : "memory");
    return v;
}
__device__ __forceinline__ float2 lds64(uint32_t a) {
    float2 v;
    asm volatile("ld.shared.v2.f32 {%0,%1}, [%2];" : "=f"(v.x), "=f"(v.y) : "r"(a) : "memory");
    return v;
}
__device__ __forceinline__ float lds32(uint32_t a) {
    float v;
    asm volatile("ld.shared.f32 %0, [%1];" : "=f"(v) : "r"(a) : "memory");
    return v;
}
__device__ __forceinline__ void sts128(uint32_t a, float x, float y, float z, float w) {
    asm volatile("st.shared.v4.f32 [%0], {%1,%2,%3,%4};" ::"r"(a), "f"(x), "f"(y), "f"(z), "f"(w) : "memory");
}
__device__ __forceinline__ void sts64(uint32_t a, float x, float y) {
    asm volatile("st.shared.v2.f32 [%0], {%1,%2};" ::"r"(a), "f"(x), "f"(y) : "memory");
}
__device__ __forceinline__ void sts32(uint32_t a, float x) {
    asm volatile("st.shared.f32 [%0], %1;" ::"r"(a), "f"(x) : "memory");
}
__device__ __forceinline__ float bf_lo(uint32_t v) { return __uint_as_float(v << 16); }
__device__ __forceinline__ float bf_hi(uint32_t v) { return __uint_as_float(v & 0xffff0000u); }
__device__ __forceinline__ float ex2(float x) {
    float r;
    asm("ex2.approx.ftz.f32 %0, %1;" : "=f"(r) : "f"(x));
    return r;
}
__device__ __forceinline__ float rcp_fast(float x) {
    float r;
    asm("rcp.approx.ftz.f32 %0, %1;" : "=f"(r) : "f"(x));
    return r;
}
__device__ __forceinline__ float sqrt_fast(float x) {
    float r;
    asm("sqrt.approx.ftz.f32 %0, %1;" : "=f"(r) : "f"(x));
    return r;
}
__device__ __forceinline__ uint32_t ld_relaxed(const unsigned int* p) {
    uint32_t v;
    asm volatile("ld.relaxed.gpu.global.u32 %0, [%1];" : "=r"(v) : "l"(p) : "memory");
    return v;
}
__device__ __forceinline__ void st_relaxed(unsigned int* p, uint32_t v) {
    asm volatile("st.relaxed.gpu.global.u32 [%0], %1;" ::"l"(p), "r"(v) : "memory");
}
__device__ __forceinline__ void mbar_init(uint32_t bar, uint32_t cnt) {
    asm volatile("mbarrier.init.shared.b64 [%0], %1;" ::"r"(bar), "r"(cnt) : "memory");
}
__device__ __forceinline__ void mbar_expect_tx(uint32_t bar, uint32_t bytes) {
    asm volatile("mbarrier.arrive.expect_tx.shared.b64 _, [%0], %1;" ::"r"(bar), "r"(bytes) : "memory");
}
__device__ __forceinline__ void mbar_arrive(uint32_t bar) {
    asm volatile("mbarrier.arrive.shared.b64 _, [%0];" ::"r"(bar) : "memory");
}
__device__ __forceinline__ bool mbar_try(uint32_t bar, uint32_t parity) {
    uint32_t ok;
    asm volatile(
        "{\n .reg .pred p;\n mbarrier.try_wait.parity.shared.b64 p, [%1], %2;\n selp.u32 %0, 1, 0, p;\n}"
        : "=r"(ok)
        : "r"(bar), "r"(parity)
        : "memory");
    return ok != 0;
}
__device__ __forceinline__ bool mbar_test(uint32_t bar, uint32_t parity) {
    uint32_t ok;
    asm volatile(
        "{\n .reg .pred p;\n mbarrier.test_wait.parity.shared.b64 p, [%1], %2;\n selp.u32 %0, 1, 0, p;\n}"
        : "=r"(ok)
        : "r"(bar), "r"(parity)
        : "memory");
    return ok != 0;
}
constexpr uint32_t SPIN_LIMIT = 1u << 24;
__device__ __forceinline__ void mbar_wait(uint32_t bar, uint32_t parity) {
    uint32_t n = 0;
    while (!mbar_try(bar, parity)) {
        if (++n > SPIN_LIMIT) __trap();
    }
}
__device__ __forceinline__ void bulk_load(uint32_t dst, const void* src, uint32_t bytes, uint32_t bar, uint64_t pol) {
    asm volatile(
        "cp.async.bulk.shared::cluster.global.mbarrier::complete_tx::bytes.L2::cache_hint [%0], [%1], %2, [%3], %4;"
        ::"r"(dst), "l"(src), "r"(bytes), "r"(bar), "l"(pol)
        : "memory");
}
__device__ __forceinline__ void tma_load_2d(uint32_t dst, const CUtensorMap* tm, int c0, int c1, uint32_t bar) {
    asm volatile(
        "cp.async.bulk.tensor.2d.shared::cluster.global.mbarrier::complete_tx::bytes [%0], [%1, {%3, %4}], [%2];"
        ::"r"(dst), "l"(tm), "r"(bar), "r"(c0), "r"(c1)
        : "memory");
}
__device__ __forceinline__ void l2_prefetch(const void* src, uint32_t bytes) {
    asm volatile("cp.async.bulk.prefetch.L2.global [%0], %1;" ::"l"(src), "r"(bytes) : "memory");
}
__device__ __forceinline__ void cp_async16(uint32_t dst, const void* src) {
    asm volatile("cp.async.cg.shared.global [%0], [%1], 16;" ::"r"(dst), "l"(src) : "memory");
}
__device__ __forceinline__ uint4 ldg_nc(const void* p) {
    uint4 v;
    asm volatile("ld.global.nc.L1::no_allocate.L2::128B.v4.u32 {%0,%1,%2,%3}, [%4];"
                 : "=r"(v.x), "=r"(v.y), "=r"(v.z), "=r"(v.w)
                 : "l"(p));
    return v;
}
__device__ __forceinline__ void ll_store(uint4* p, uint32_t a, uint32_t b, uint32_t c, uint32_t tag) {
    asm volatile(
        "{\n .reg .b128 t;\n .reg .b64 lo, hi;\n mov.b64 lo, {%1, %2};\n mov.b64 hi, {%3, %4};\n"
        " mov.b128 t, {lo, hi};\n st.relaxed.gpu.global.b128 [%0], t;\n}"
        ::"l"(p), "r"(a), "r"(b), "r"(c), "r"(tag)
        : "memory");
}
__device__ __forceinline__ uint4 ll_load(const uint4* p) {
    uint4 v;
    asm volatile(
        "{\n .reg .b128 t;\n .reg .b64 lo, hi;\n ld.relaxed.gpu.global.b128 t, [%4];\n"
        " mov.b128 {lo, hi}, t;\n mov.b64 {%0, %1}, lo;\n mov.b64 {%2, %3}, hi;\n}"
        : "=r"(v.x), "=r"(v.y), "=r"(v.z), "=r"(v.w)
        : "l"(p)
        : "memory");
    return v;
}
__device__ __forceinline__ void ldsm4(uint32_t (&r)[4], uint32_t addr) {
    asm volatile("ldmatrix.sync.aligned.m8n8.x4.shared.b16 {%0,%1,%2,%3}, [%4];"
                 : "=r"(r[0]), "=r"(r[1]), "=r"(r[2]), "=r"(r[3])
                 : "r"(addr)
                 : "memory");
}
__device__ __forceinline__ void ldsm4t(uint32_t (&r)[4], uint32_t addr) {
    asm volatile("ldmatrix.sync.aligned.m8n8.x4.trans.shared.b16 {%0,%1,%2,%3}, [%4];"
                 : "=r"(r[0]), "=r"(r[1]), "=r"(r[2]), "=r"(r[3])
                 : "r"(addr)
                 : "memory");
}
__device__ __forceinline__ void mma16816(float (&c)[4], uint32_t a0, uint32_t a1, uint32_t a2, uint32_t a3,
                                         uint32_t b0, uint32_t b1) {
    asm volatile(
        "mma.sync.aligned.m16n8k16.row.col.f32.bf16.bf16.f32 {%0,%1,%2,%3}, {%4,%5,%6,%7}, {%8,%9}, {%0,%1,%2,%3};"
        : "+f"(c[0]), "+f"(c[1]), "+f"(c[2]), "+f"(c[3])
        : "r"(a0), "r"(a1), "r"(a2), "r"(a3), "r"(b0), "r"(b1));
}
__device__ __forceinline__ void bar_sync(int id, int n) {
    __syncwarp();
    asm volatile("bar.sync %0, %1;" ::"r"(id), "r"(n) : "memory");
}
__device__ __forceinline__ float warp_max(float v) {
    int k = __float_as_int(v);
    k ^= (k >> 31) & 0x7fffffff;
    k = __reduce_max_sync(0xffffffffu, k);
    k ^= (k >> 31) & 0x7fffffff;
    return __int_as_float(k);
}
#define TL_DECL
#define TL_STAMP(i)
#define TL_FLUSH()

__device__ __forceinline__ void ln_stats(const float* v, int lane, float& mean_b, float& sd_b) {
    const float4* v4 = reinterpret_cast<const float4*>(v);
    float piv = v[0];
    float s1 = 0.f, s2 = 0.f;
#pragma unroll
    for (int i = 0; i < 5; i++) {
        float4 a = v4[lane + 32 * i];
        float d0 = a.x - piv, d1 = a.y - piv, d2 = a.z - piv, d3 = a.w - piv;
        s1 += (d0 + d1) + (d2 + d3);
        s2 += (d0 * d0 + d1 * d1) + (d2 * d2 + d3 * d3);
    }
#pragma unroll
    for (int o = 16; o > 0; o >>= 1) {
        s1 += __shfl_xor_sync(0xffffffffu, s1, o);
        s2 += __shfl_xor_sync(0xffffffffu, s2, o);
    }
    float md = s1 * (1.0f / DM);
    float var = fmaxf(s2 * (1.0f / DM) - md * md, 0.f);
    mean_b = bfr(piv + md);
    sd_b = bfr(__fsqrt_rn(bfr(bfr(var) + 1e-5f)));
}
__device__ __forceinline__ float ln_apply(float x, float mean_b, float sd_b) {
    return bfr(__fdiv_rn(bfr(x - mean_b), sd_b));
}

struct Params {
    const __nv_bfloat16* x;
    const char* k;
    const char* v;
    const __nv_bfloat16* wq;
    const __nv_bfloat16* wo;
    const __nv_bfloat16* wg;
    const __nv_bfloat16* wu;
    const __nv_bfloat16* wd;
    __nv_bfloat16* out;
};

__global__ void __launch_bounds__(NTHREADS, 1)
fused_kernel(const Params p, const __grid_constant__ CUtensorMap tm_wq) {
    extern __shared__ __align__(1024) unsigned char smem[];
    const uint32_t sb = opaque(s2u(smem));
    const int tid = threadIdx.x, warp = tid >> 5, lane = tid & 31;
    const int g = lane >> 2, j = lane & 3;
    const int NS = gridDim.x - NCOMB;
    const int cta = blockIdx.x;
    const uint32_t bar_full = sb + SM_BAR, bar_empty = sb + SM_BAR + 8 * NSLOT, bar_wq = sb + SM_BAR + 16 * NSLOT;
    const uint32_t bar_q = bar_wq + 16;
    volatile int* meta = reinterpret_cast<volatile int*>(smem + SM_META);
    volatile uint32_t* tag_s = reinterpret_cast<volatile uint32_t*>(smem + SM_TAG);
    TL_DECL

    if (cta < NS) {
        if (warp == 8) {
            if (lane == 0) {
                TL_STAMP(0);
                asm volatile("prefetch.tensormap [%0];" ::"l"(&tm_wq) : "memory");
                for (int s = 0; s < NSLOT; s++) {
                    mbar_init(bar_full + 8 * s, 1);
                    mbar_init(bar_empty + 8 * s, 4);
                }
                mbar_init(bar_wq, 1);
                mbar_init(bar_wq + 8, 1);
                mbar_init(bar_q, 4);
                asm volatile("fence.mbarrier_init.release.cluster;" ::: "memory");
            }
            __syncwarp();
            asm volatile("bar.arrive 1, 320;" ::: "memory");
            if (lane == 0) {
                uint64_t pol;
                asm volatile("createpolicy.fractional.L2::evict_first.b64 %0, 1.0;" : "=l"(pol));
#pragma unroll
                for (int e = 0; e < 2 + NSLOT + 2 * NPF; e++) {
                    const int w = e - START_W;
                    if (w >= 0 && w < 2 + NSLOT) mbar_wait(w < 2 ? bar_wq + 8 * w : bar_full + 8 * (w - 2), 0);
                    if (e == 2 + START_W) TL_STAMP(9);
                    if (e == 4 + START_W) TL_STAMP(10);
                    if (e < 2) {
                        mbar_expect_tx(bar_wq + 8 * e, DM * 48);
                        tma_load_2d(sb + SM_WQ + (2 * e) * WQ_BOX_ROWS * 96, &tm_wq, cta * 48, (2 * e) * WQ_BOX_ROWS, bar_wq + 8 * e);
                        tma_load_2d(sb + SM_WQ + (2 * e + 1) * WQ_BOX_ROWS * 96, &tm_wq, cta * 48, (2 * e + 1) * WQ_BOX_ROWS, bar_wq + 8 * e);
                    } else {
                        const int c = e - 2, item = cta + NS * (c >> 1);
                        const char* src = ((c & 1) ? p.v : p.k) + (size_t)item * CHUNK;
                        if (c < NSLOT) {
                            if (!(c & 1)) meta[c >> 1] = item;
                            mbar_expect_tx(bar_full + 8 * c, CHUNK);
                            bulk_load(sb + SM_RING + c * CHUNK, src, CHUNK, bar_full + 8 * c, pol);
                        } else {
                            l2_prefetch(src, CHUNK);
                        }
                    }
                }
                int n = NPRE;
                int slot = 0;
                uint32_t ph = 1;
                int lslot = NSLOT - 2;
                uint32_t lph = 0;
                while (true) {
                    mbar_wait(bar_full + 8 * lslot, lph);
                    mbar_wait(bar_empty + 8 * slot, ph ^ 1);
                    const int item = n < NPRE + NPF ? cta + NS * n : NS * (NPRE + NPF) + (int)atomicAdd(&g_work, 1u);
                    if (item >= NITEMS) break;
                    meta[slot >> 1] = item;
                    mbar_expect_tx(bar_full + 8 * slot, CHUNK);
                    bulk_load(sb + SM_RING + slot * CHUNK, p.k + (size_t)item * CHUNK, CHUNK, bar_full + 8 * slot, pol);
                    mbar_wait(bar_empty + 8 * slot + 8, ph ^ 1);
                    mbar_expect_tx(bar_full + 8 * slot + 8, CHUNK);
                    bulk_load(sb + SM_RING + (slot + 1) * CHUNK, p.v + (size_t)item * CHUNK, CHUNK, bar_full + 8 * slot + 8, pol);
                    lslot = slot;
                    lph = ph;
                    slot += 2;
                    if (slot == NSLOT) { slot = 0; ph ^= 1; }
                    n++;
                }
                meta[slot >> 1] = -1;
                mbar_arrive(bar_full + 8 * slot);
                TL_STAMP(1);
                unsigned int e = atomicAdd(&g_exit, 1u);
                if (e == (unsigned)NS - 1) {
                    *(volatile unsigned int*)&g_work = 0;
                    *(volatile unsigned int*)&g_exit = 0;
                }
                TL_FLUSH();
            }
            return;
        }
        float* xs = reinterpret_cast<float*>(smem + SM_XS);
        if (warp == 9) {
            uint2 xv[5];
#pragma unroll
            for (int i = 0; i < 5; i++) xv[i] = *reinterpret_cast<const uint2*>(p.x + 4 * (lane + 32 * i));
            if (lane == 0) *tag_s = *(volatile unsigned int*)&g_epoch + 1;
#pragma unroll
            for (int i = 0; i < 5; i++)
                *reinterpret_cast<float4*>(xs + 4 * (lane + 32 * i)) =
                    make_float4(bf_lo(xv[i].x), bf_hi(xv[i].x), bf_lo(xv[i].y), bf_hi(xv[i].y));
            __syncwarp();
            float mean_b, sd_b;
            ln_stats(xs, lane, mean_b, sd_b);
#pragma unroll
            for (int i = 0; i < 5; i++)
                *reinterpret_cast<uint2*>(smem + SM_XN + 8 * (lane + 32 * i)) =
                    make_uint2(pack_bf2(ln_apply(bf_lo(xv[i].x), mean_b, sd_b), ln_apply(bf_hi(xv[i].x), mean_b, sd_b)),
                               pack_bf2(ln_apply(bf_lo(xv[i].y), mean_b, sd_b), ln_apply(bf_hi(xv[i].y), mean_b, sd_b)));
            __syncwarp();
            if (lane == 0) TL_STAMP(13);
            asm volatile("bar.arrive 1, 320;" ::: "memory");
            TL_FLUSH();
            return;
        }
        float* qred = reinterpret_cast<float*>(smem + SM_QRED);
        const int dn_idx = cta - (NS - NDN);
        if (tid < 8)
            for (int slice = cta; slice < NQS; slice += NS) ll_store(&g_q[slice * 8 + tid], 0u, 0u, 0u, 0u);
        if (warp == 4 && lane < 8 && !(lane & 1) && cta < NGU) ll_store(&g_act[cta][lane >> 1], 0u, 0u, 0u, 0u);
        bar_sync(1, 320);
        const uint32_t tag = *tag_s;
        if (tid == 0) TL_STAMP(12);
        for (int slice = cta, it = 0; slice < NQS; slice += NS, it++) {
            if (it > 0) {
                bar_sync(2, 256);
                if (tid == 0) {
                    mbar_expect_tx(bar_wq, DM * 48);
                    mbar_expect_tx(bar_wq + 8, DM * 48);
                    for (int i = 0; i < DM / WQ_BOX_ROWS; i++)
                        tma_load_2d(sb + SM_WQ + i * WQ_BOX_ROWS * 96, &tm_wq, slice * 48, i * WQ_BOX_ROWS, bar_wq + 8 * (i >> 1));
                }
            }
            const uint32_t* xn = reinterpret_cast<const uint32_t*>(smem + SM_XN) + 40 * warp + j;
            const uint32_t wa = sb + SM_WQ + (80 * warp + (lane & 7) + 8 * (lane >> 4)) * 96 + ((lane >> 3) & 1) * 16;
            float c[3][4];
#pragma unroll
            for (int t = 0; t < 3; t++) c[t][0] = c[t][1] = c[t][2] = c[t][3] = 0.f;
            mbar_wait(bar_wq + 8 * (warp >> 2), it & 1);
            if (tid == 128) TL_STAMP(14);
#pragma unroll
            for (int s = 0; s < 5; s++) {
                const uint32_t b0 = xn[8 * s], b1 = xn[8 * s + 4];
#pragma unroll
                for (int t = 0; t < 3; t++) {
                    uint32_t a[4];
                    ldsm4t(a, wa + s * 16 * 96 + t * 32);
                    mma16816(c[t], a[0], a[1], a[2], a[3], b0, b1);
                }
            }
            if (j < 3) {
                qred[warp * 48 + 16 * j + g] = j == 0 ? c[0][0] : j == 1 ? c[1][0] : c[2][0];
                qred[warp * 48 + 16 * j + g + 8] = j == 0 ? c[0][2] : j == 1 ? c[1][2] : c[2][2];
            }
            bar_sync(2, 256);
            if (tid == 0) TL_STAMP(15);
            if (warp == 0) {
                float2 s = make_float2(0.f, 0.f);
                const int pi = lane < 24 ? lane : 0;
#pragma unroll
                for (int w8 = 0; w8 < 8; w8++) {
                    float2 v = *reinterpret_cast<const float2*>(qred + w8 * 48 + 2 * pi);
                    s.x += v.x;
                    s.y += v.y;
                }
                const uint32_t pk = pack_bf2(s.x, s.y);
                const uint32_t p0 = __shfl_sync(0xffffffffu, pk, 3 * (lane & 7));
                const uint32_t p1 = __shfl_sync(0xffffffffu, pk, 3 * (lane & 7) + 1);
                const uint32_t p2 = __shfl_sync(0xffffffffu, pk, 3 * (lane & 7) + 2);
                if (lane < 8) ll_store(&g_q[slice * 8 + lane], p0, p1, p2, tag);
            }
        }
        if (tid == 0) TL_STAMP(2);
        bar_sync(2, 256);
        {
            uint32_t* qs = reinterpret_cast<uint32_t*>(smem + SM_Q);
            uint32_t n = 0;
            if (warp == 0) {
                uint4 u;
                while ((u = ll_load(&g_q[lane])).w != tag) {
                    if (++n > SPIN_LIMIT) __trap();
                }
                qs[3 * lane] = u.x;
                qs[3 * lane + 1] = u.y;
                qs[3 * lane + 2] = u.z;
            } else if (warp >= 4) {
                uint4 u[8];
#pragma unroll
                for (int i = 0; i < 8; i++) u[i].w = 0u;
                while (true) {
                    bool ok = true;
#pragma unroll
                    for (int i = 0; i < 8; i++)
                        if (u[i].w != tag) u[i] = ll_load(&g_q[tid - 128 + 128 * i]);
#pragma unroll
                    for (int i = 0; i < 8; i++) ok = ok && (u[i].w == tag);
                    if (ok) break;
                    if (++n > SPIN_LIMIT) __trap();
                    __nanosleep(200);
                }
#pragma unroll
                for (int i = 0; i < 8; i++) {
                    const int un = tid - 128 + 128 * i;
                    if (un >= 32) {
                        qs[3 * un] = u[i].x;
                        qs[3 * un + 1] = u[i].y;
                        qs[3 * un + 2] = u[i].z;
                    }
                }
                __syncwarp();
                if (lane == 0) mbar_arrive(bar_q);
            }
            if (warp < 4) bar_sync(3, 128);
        }
        if (tid == 0) TL_STAMP(3);

        if (warp < 4) {
            const int mi = lane >> 3, r = lane & 7;
            uint32_t offK[4], offV[4];
            {
                int keyK = 16 * warp + r + 8 * (mi & 1), zK = (mi >> 1) ^ r;
                int keyV = 16 * warp + r + 8 * (mi >> 1), zV = (mi & 1) ^ r;
#pragma unroll
                for (int u = 0; u < 4; u++) {
                    offK[u] = sb + SM_RING + keyK * ROWB + (((2 * u) ^ zK) << 4);
                    offV[u] = sb + SM_RING + keyV * ROWB + (((2 * u) ^ zV) << 4);
                }
            }
            const bool valid = (j == (g >> 1));
            const bool odd = g & 1;
            float acc[12][4];
#pragma unroll
            for (int t = 0; t < 12; t++) acc[t][0] = acc[t][1] = acc[t][2] = acc[t][3] = 0.f;
            float m_run = NEG_INF, l_run = 0.f;
            uint32_t qf[12][2];
            int cur = -1;
            int pub = 0;
            int slot = 0;
            uint32_t ph = 0;
            uint4* pub_p = tid < 64 ? &g_pdat[0][tid >> 4][cta][tid & 15] : &g_phdr[0][cta];
            const int pub_step = tid < 64 ? NCOMB * MAXS * 16 : MAXS;
            const uint32_t a_ow = sb + SM_OBUF + (warp * DH + 16 * j + g) * 4;
            const uint32_t a_or = sb + SM_OBUF + (tid < 64 ? 12 * tid : 0);
            const uint32_t* qs = reinterpret_cast<const uint32_t*>(smem + SM_Q);

            while (true) {
                mbar_wait(bar_full + 8 * slot, ph);
                const int item = meta[slot >> 1];
                const int head = item < 0 ? NH : item / ITEMS_PER_HEAD;
                if (head != cur) {
                    while (pub < head) {
                        const uint32_t par = pub & 1;
                        pub_p = opaque(pub_p);
                        float l = l_run;
                        l += __shfl_xor_sync(0xffffffffu, l, 16);
                        float w0[6], w2[6];
#pragma unroll
                        for (int T = 0; T < 3; T++) {
#pragma unroll
                            for (int b = 0; b < 2; b++) {
                                float v0 = b ? acc[4 * T + 0][1] + acc[4 * T + 0][2] : acc[4 * T + 0][0] + acc[4 * T + 0][3];
                                float v1 = b ? acc[4 * T + 1][1] + acc[4 * T + 1][2] : acc[4 * T + 1][0] + acc[4 * T + 1][3];
                                float v2 = b ? acc[4 * T + 2][1] + acc[4 * T + 2][2] : acc[4 * T + 2][0] + acc[4 * T + 2][3];
                                float v3 = b ? acc[4 * T + 3][1] + acc[4 * T + 3][2] : acc[4 * T + 3][0] + acc[4 * T + 3][3];
                                w0[2 * T + b] = v0 + __shfl_xor_sync(0xffffffffu, v1, 1);
                                w2[2 * T + b] = v2 + __shfl_xor_sync(0xffffffffu, v3, 1);
                            }
                        }
                        l += __shfl_xor_sync(0xffffffffu, l, 8);
#pragma unroll
                        for (int i = 0; i < 6; i++) w0[i] += __shfl_xor_sync(0xffffffffu, w2[i], 2);
                        l += __shfl_xor_sync(0xffffffffu, l, 4);
#pragma unroll
                        for (int i = 0; i < 6; i++) sts32(a_ow + par * (4 * DH * 4) + ((i >> 1) * 64 + (i & 1) * 8) * 4, w0[i]);
                        if (lane < 4) sts32(sb + SM_ML + par * 80 + 16 + warp * 16 + lane * 4, l);
                        if (lane == 0) sts32(sb + SM_ML + par * 80 + warp * 4, m_run);
                        bar_sync(3, 128);
                        if (tid <= 64) {
                            const float4 m4 = lds128(sb + SM_ML + par * 80);
                            float ov[4][3];
                            float4 l4[4];
#pragma unroll
                            for (int w4 = 0; w4 < 4; w4++) {
                                if (tid < 64) {
#pragma unroll
                                    for (int e = 0; e < 3; e++) ov[w4][e] = lds32(a_or + par * (4 * DH * 4) + (w4 * DH + e) * 4);
                                } else {
                                    l4[w4] = lds128(sb + SM_ML + par * 80 + 16 + w4 * 16);
                                    ov[w4][0] = 0.f;
                                    ov[w4][1] = (l4[w4].x + l4[w4].y) + (l4[w4].z + l4[w4].w);
                                    ov[w4][2] = 0.f;
                                }
                            }
                            const float M = fmaxf(fmaxf(m4.x, m4.y), fmaxf(m4.z, m4.w));
                            const float Ms = M == NEG_INF ? 0.f : M;
                            const float f0 = ex2((m4.x - Ms) * LOG2E), f1 = ex2((m4.y - Ms) * LOG2E);
                            const float f2 = ex2((m4.z - Ms) * LOG2E), f3 = ex2((m4.w - Ms) * LOG2E);
                            float r3[3];
#pragma unroll
                            for (int e = 0; e < 3; e++)
                                r3[e] = fmaf(f0, ov[0][e], f1 * ov[1][e]) + fmaf(f2, ov[2][e], f3 * ov[3][e]);
                            ll_store(pub_p, __float_as_uint(tid < 64 ? r3[0] : M), __float_as_uint(r3[1]),
                                     __float_as_uint(r3[2]), tag);
                        }
                        pub_p += pub_step;
#pragma unroll
                        for (int t = 0; t < 12; t++) acc[t][0] = acc[t][1] = acc[t][2] = acc[t][3] = 0.f;
                        m_run = NEG_INF;
                        l_run = 0.f;
                        pub++;
                    }
                    if (item < 0) break;
                    if (head > 0) mbar_wait(bar_q, 0);
                    cur = head;
                    const uint32_t* qh = qs + head * (DH / 2) + j;
#pragma unroll
                    for (int t = 0; t < 12; t++) {
                        qf[t][0] = qh[((t >> 2) * 8 + ((2 * (t & 3)) ^ g)) * 4];
                        qf[t][1] = qh[((t >> 2) * 8 + ((2 * (t & 3) + 1) ^ g)) * 4];
                    }
                }
                const uint32_t so = slot * CHUNK;
                float s0[4] = {0.f, 0.f, 0.f, 0.f}, s1[4] = {0.f, 0.f, 0.f, 0.f};
#pragma unroll
                for (int t = 0; t < 12; t += 2) {
                    uint32_t a[4], b[4];
                    ldsm4(a, offK[t & 3] + so + (t >> 2) * 128);
                    ldsm4(b, offK[(t + 1) & 3] + so + ((t + 1) >> 2) * 128);
                    mma16816(s0, a[0], a[1], a[2], a[3], qf[t][0], qf[t][1]);
                    mma16816(s1, b[0], b[1], b[2], b[3], qf[t + 1][0], qf[t + 1][1]);
                }
                __syncwarp();
                if (lane == 0) mbar_arrive(bar_empty + 8 * slot);
                float sa = odd ? s0[1] + s1[1] : s0[0] + s1[0];
                float sb2 = odd ? s0[3] + s1[3] : s0[2] + s1[2];
                sa = valid ? bfr(bfr(sa) * QK_SCALE) : NEG_INF;
                sb2 = valid ? bfr(bfr(sb2) * QK_SCALE) : NEG_INF;
                const float mx = warp_max(fmaxf(sa, sb2));
                if (mx > m_run) {
                    const float al = ex2((m_run - mx) * LOG2E);
#pragma unroll
                    for (int t = 0; t < 12; t++) {
                        acc[t][0] *= al;
                        acc[t][1] *= al;
                        acc[t][2] *= al;
                        acc[t][3] *= al;
                    }
                    l_run *= al;
                    m_run = mx;
                }
                const float pa = ex2((sa - m_run) * LOG2E), pb = ex2((sb2 - m_run) * LOG2E);
                uint32_t b0 = 0, b1 = 0;
                if (valid) {
                    l_run += pa + pb;
                    b0 = odd ? pack_bf2(0.f, pa) : pack_bf2(pa, 0.f);
                    b1 = odd ? pack_bf2(0.f, pb) : pack_bf2(pb, 0.f);
                }
                mbar_wait(bar_full + 8 * (slot + 1), ph);
#pragma unroll
                for (int t = 0; t < 12; t++) {
                    uint32_t a[4];
                    ldsm4t(a, offV[t & 3] + so + CHUNK + (t >> 2) * 128);
                    mma16816(acc[t], a[0], a[1], a[2], a[3], b0, b1);
                }
                __syncwarp();
                if (lane == 0) mbar_arrive(bar_empty + 8 * (slot + 1));
                slot += 2;
                if (slot == NSLOT) { slot = 0; ph ^= 1; }
            }
            if (tid == 0) TL_STAMP(4);
        } else {
            if (tid == 128) {
                constexpr int PIECE = DM * FF * 2 / 128;
                for (int i = cta; i < 128; i += NS) {
                    l2_prefetch(reinterpret_cast<const char*>(p.wg) + i * PIECE, PIECE);
                    l2_prefetch(reinterpret_cast<const char*>(p.wu) + i * PIECE, PIECE);
                    l2_prefetch(reinterpret_cast<const char*>(p.wd) + i * PIECE, PIECE);
                }
            }
            for (int i = 0; i < 10; i++) __nanosleep(1000);
            const int ht = tid - 128;
            if (cta < NGU) {
#pragma unroll
                for (int i = 0; i < 10; i++) {
                    int e = ht + 128 * i;
                    size_t off = (size_t)(e >> 1) * FF + cta * 16 + (e & 1) * 8;
                    const int sw = (e ^ ((e >> 4) & 7)) * 16;
                    cp_async16(sb + SM_WG + sw, p.wg + off);
                    cp_async16(sb + SM_WU + sw, p.wu + off);
                }
            }
            if (dn_idx >= 0) {
#pragma unroll
                for (int i = 0; i < 12; i++) {
                    int e = ht + 128 * i;
                    cp_async16(sb + SM_WD + e * 16, p.wd + (size_t)e * DM + dn_idx * 8);
                }
            }
            asm volatile("cp.async.commit_group;" ::: "memory");
            asm volatile("cp.async.wait_group 0;" ::: "memory");
            bar_sync(4, 128);
            if (warp == 4 && cta < NGU) {
                const unsigned short* wsm =
                    reinterpret_cast<const unsigned short*>(smem + (lane < 16 ? SM_WG : SM_WU)) + (lane & 7);
                const int half = (lane >> 3) & 1;
                float s0 = 0.f, s1 = 0.f;
#pragma unroll 8
                for (int k = 0; k < DM; k += 2) {
                    s0 += __uint_as_float((uint32_t)wsm[((2 * k + half) ^ ((k >> 3) & 7)) * 8] << 16);
                    s1 += __uint_as_float((uint32_t)wsm[((2 * k + 2 + half) ^ ((k >> 3) & 7)) * 8] << 16);
                }
                reinterpret_cast<float*>(smem + SM_CS)[(lane & 15) * 2 + (lane >> 4)] = s0 + s1;
            }
        }
#define CK_STAMP(i)
        int pass = warp < 4 ? NDRY : 0;
#pragma unroll 1
        for (; pass <= NDRY; pass++) {
            asm volatile("" : "+r"(pass));
            const bool live = pass == NDRY;
            const int bid = live ? 2 : 4, bcnt = live ? 256 : 128;
            bar_sync(bid, bcnt);
            CK_STAMP(0);
            uint32_t wgf[5][4], wuf[5][4], wdf[6][4];
            const bool gu = cta < NGU;
            auto ucol = [](int U, int e) { return U < 16 ? 8 * (4 * (U >> 3) + e) + (U & 7) : 8 * (8 + (e & 1)) + 2 * (U - 16) + (e >> 1); };
            {
                const int mi = lane >> 3, r = lane & 7;
                if (gu) {
#pragma unroll
                    for (int s = 0; s < 5; s++) {
                        const int row = 80 * warp + ucol(4 * s + (r >> 1), 2 * (mi >> 1) + (r & 1));
                        const uint32_t off = ((2 * row + (mi & 1)) ^ ((row >> 3) & 7)) * 16;
                        ldsm4t(wgf[s], sb + SM_WG + off);
                        ldsm4t(wuf[s], sb + SM_WU + off);
                    }
                }
                if (dn_idx >= 0) {
                    const uint32_t wa = sb + SM_WD + (192 * warp + 16 * (mi & 1) + 4 * (r >> 1) + 2 * (mi >> 1) + (r & 1)) * 16;
#pragma unroll
                    for (int s = 0; s < 6; s++) ldsm4t(wdf[s], wa + s * 512);
                }
            }
            const int U = lane < 20 ? lane : 0;
            const uint4* attn_p = opaque(live ? &g_attn[0][warp][U] : &g_q[U]);
            uint4* act_st = opaque(live ? &g_act[gu ? cta : 0][(lane >> 1) & 3] : &g_dummy[lane]);
            const uint4* act_p0 = opaque(live ? &g_act[12 * warp + g][j] : &g_q[lane]);
            const uint4* act_p1 = opaque(live ? &g_act[12 * warp + 8 + (g & 3)][j] : &g_q[lane]);
            __nv_bfloat16* out_p = opaque(live ? p.out + (dn_idx >= 0 ? dn_idx * 8 : 0) + (lane & 7)
                                               : reinterpret_cast<__nv_bfloat16*>(&g_dummy[32 + lane]));
            const unsigned int* bell_p = opaque(live ? &g_bell[(cta * 8 + warp) & 31][j] : &g_q[j].x);
            const uint32_t a_h = opaque(sb + SM_H + (80 * warp + ucol(U, 0)) * 4);
            const uint32_t a_red = opaque(sb + SM_RED + warp * 128 + (g + 8 * (j & 1)) * 8);
            const uint32_t a_fin = opaque(sb + SM_RED + (lane & 7) * 16);
            const uint32_t a_r2 = opaque(sb + SM_RED2 + g * 32 + warp * 4);
            const uint32_t a_f2 = opaque(sb + SM_RED2 + (lane & 7) * 32);
            const uint32_t a_ho = opaque(sb + SM_H + ((dn_idx >= 0 ? dn_idx * 8 : 0) + (lane & 7)) * 4);
            const uint32_t tag4 = tag & 15u;
            if (gu || warp == dn_idx / 10) {
                float xr[4];
#pragma unroll
                for (int e = 0; e < 4; e++) xr[e] = __bfloat162float(p.x[80 * warp + ucol(U, e)]);
                uint32_t n = 0;
                while (!__all_sync(0xffffffffu, ld_relaxed(bell_p) == tag) && live) {
                    if (++n > SPIN_LIMIT) __trap();
                }
                uint4 u[4];
                while (true) {
#pragma unroll
                    for (int q = 0; q < 4; q++) u[q] = ll_load(attn_p + q * 256);
                    const uint32_t bad = (u[0].w ^ tag4) | (u[1].w ^ tag4) | (u[2].w ^ tag4) | (u[3].w ^ tag4);
                    if (__all_sync(0xffffffffu, (bad & 15u) == 0) || !live) break;
                    if (++n > SPIN_LIMIT) __trap();
                }
                if (tid == 128) TL_STAMP(8);
                CK_STAMP(1);
                const float a0 = (__uint_as_float(u[0].x) + __uint_as_float(u[1].x)) + (__uint_as_float(u[2].x) + __uint_as_float(u[3].x));
                const float a1 = (__uint_as_float(u[0].y) + __uint_as_float(u[1].y)) + (__uint_as_float(u[2].y) + __uint_as_float(u[3].y));
                const float a2 = (__uint_as_float(u[0].z) + __uint_as_float(u[1].z)) + (__uint_as_float(u[2].z) + __uint_as_float(u[3].z));
                const float a3 = (__uint_as_float(u[0].w ^ tag4) + __uint_as_float(u[1].w ^ tag4)) +
                                 (__uint_as_float(u[2].w ^ tag4) + __uint_as_float(u[3].w ^ tag4));
                const uint32_t hb0 = pack_bf2(xr[0] + bfr(a0), xr[1] + bfr(a1));
                const uint32_t hb1 = pack_bf2(xr[2] + bfr(a2), xr[3] + bfr(a3));
                const float h0 = bf_lo(hb0), h1 = bf_hi(hb0), h2 = bf_lo(hb1), h3 = bf_hi(hb1);
                if (gu) {
                    uint32_t b0[5], b1[5];
                    const float piv = __shfl_sync(0xffffffffu, h0, 0);
#pragma unroll
                    for (int s = 0; s < 5; s++) {
                        b0[s] = __shfl_sync(0xffffffffu, hb0, 4 * s + j);
                        b1[s] = __shfl_sync(0xffffffffu, hb1, 4 * s + j);
                    }
                    const float d0 = h0 - piv, d1 = h1 - piv, d2 = h2 - piv, d3 = h3 - piv;
                    float s1 = lane < 20 ? (d0 + d1) + (d2 + d3) : 0.f;
                    float s2 = lane < 20 ? fmaf(d0, d0, d1 * d1) + fmaf(d2, d2, d3 * d3) : 0.f;
                    float cg[2][4], cu[2][4];
#pragma unroll
                    for (int i = 0; i < 2; i++) {
                        cg[i][0] = cg[i][1] = cg[i][2] = cg[i][3] = 0.f;
                        cu[i][0] = cu[i][1] = cu[i][2] = cu[i][3] = 0.f;
                    }
#pragma unroll
                    for (int s = 0; s < 5; s++) {
                        const float t1 = __shfl_xor_sync(0xffffffffu, s1, 16 >> s);
                        const float t2 = __shfl_xor_sync(0xffffffffu, s2, 16 >> s);
                        mma16816(cg[s & 1], wgf[s][0], wgf[s][1], wgf[s][2], wgf[s][3], b0[s], b1[s]);
                        mma16816(cu[s & 1], wuf[s][0], wuf[s][1], wuf[s][2], wuf[s][3], b0[s], b1[s]);
                        s1 += t1;
                        s2 += t2;
                    }
                    const bool o1 = j & 1;
                    const float ga = o1 ? cg[0][2] + cg[1][2] : cg[0][0] + cg[1][0];
                    const float ua = o1 ? cu[0][2] + cu[1][2] : cu[0][0] + cu[1][0];
                    if (live) {
                        if (j < 2) sts64(a_red, ga, ua);
                        if (lane == 0) sts128(sb + SM_ST + warp * 16, fmaf(80.f, piv, s1), piv, 2.f * s1, s2);
                    }
                }
                if (live && lane < 20) {
                    sts32(a_h, h0);
                    sts32(a_h + 32, h1);
                    sts32(a_h + (U < 16 ? 64 : 4), h2);
                    sts32(a_h + (U < 16 ? 96 : 36), h3);
                }
            }
            CK_STAMP(2);
            bar_sync(bid, bcnt);
            if (tid == 128) TL_STAMP(5);
            CK_STAMP(3);
            if (gu && warp == 4) {
                float4 st[8], ra[8];
#pragma unroll
                for (int w8 = 0; w8 < 8; w8++) st[w8] = lds128(sb + SM_ST + w8 * 16);
#pragma unroll
                for (int w8 = 0; w8 < 8; w8++) ra[w8] = lds128(a_fin + w8 * 128);
                const float4 cs = lds128(a_fin + (SM_CS - SM_RED));
#define SUM8(arr, f) (((arr[0].f + arr[1].f) + (arr[2].f + arr[3].f)) + ((arr[4].f + arr[5].f) + (arr[6].f + arr[7].f)))
                const float mean = SUM8(st, x) * (1.0f / DM);
#pragma unroll
                for (int w8 = 0; w8 < 8; w8++) {
                    const float dl = st[w8].y - mean;
                    st[w8].w = fmaf(dl, fmaf(80.f, dl, st[w8].z), st[w8].w);
                }
                const float var = fmaxf(SUM8(st, w) * (1.0f / DM), 0.f);
                const float rs = rcp_fast(bfr(sqrt_fast(bfr(bfr(var) + 1e-5f))));
                const float mean_b = bfr(mean);
                const float g0 = bfr(fmaf(-mean_b, cs.x, SUM8(ra, x)) * rs), u0 = bfr(fmaf(-mean_b, cs.y, SUM8(ra, y)) * rs);
                const float g1 = bfr(fmaf(-mean_b, cs.z, SUM8(ra, z)) * rs), u1 = bfr(fmaf(-mean_b, cs.w, SUM8(ra, w)) * rs);
#undef SUM8
                const float act0 = bfr(g0 * rcp_fast(1.0f + ex2(-LOG2E * g0))) * u0;
                const float act1 = bfr(g1 * rcp_fast(1.0f + ex2(-LOG2E * g1))) * u1;
                const uint32_t pk = pack_bf2(act0, act1);
                const uint32_t pn = __shfl_down_sync(0xffffffffu, pk, 1);
                if (lane < 8 && !(lane & 1)) ll_store(act_st, pk, pn, 0u, tag);
                if (lane == 0) TL_STAMP(6);
                CK_STAMP(7);
            }
            if (dn_idx >= 0) {
                const float hres = lds32(a_ho);
                uint4 u0, u1;
                uint32_t n = 0;
                while (true) {
                    u0 = ll_load(act_p0);
                    u1 = ll_load(act_p1);
                    if (__all_sync(0xffffffffu, u0.w == tag && u1.w == tag) || !live) break;
                    if (++n > SPIN_LIMIT) __trap();
                }
                if (tid == 128) TL_STAMP(11);
                CK_STAMP(8);
                float c[3][4];
#pragma unroll
                for (int i = 0; i < 3; i++) c[i][0] = c[i][1] = c[i][2] = c[i][3] = 0.f;
#pragma unroll
                for (int i = 0; i < 6; i++) {
                    const bool on = (g >> 1) == (i < 4 ? i : i - 4);
                    const uint32_t b0 = on ? (i < 4 ? u0.x : u1.x) : 0u, b1 = on ? (i < 4 ? u0.y : u1.y) : 0u;
                    mma16816(c[i % 3], wdf[i][0], wdf[i][1], wdf[i][2], wdf[i][3], b0, b1);
                }
                float e0 = ((c[0][0] + c[0][3]) + (c[1][0] + c[1][3])) + (c[2][0] + c[2][3]);
                e0 += __shfl_xor_sync(0xffffffffu, e0, 1);
                e0 += __shfl_xor_sync(0xffffffffu, e0, 2);
                if (j == 0 && live) sts32(a_r2, e0);
                CK_STAMP(9);
                bar_sync(bid, bcnt);
                CK_STAMP(10);
                if (warp == 4 && lane < 8) {
                    const float4 ra = lds128(a_f2), rb = lds128(a_f2 + 16);
                    const float sum = ((ra.x + ra.y) + (ra.z + ra.w)) + ((rb.x + rb.y) + (rb.z + rb.w));
                    const uint32_t res = pack_bf2(hres + bfr(sum), 0.f);
                    asm volatile("st.global.u16 [%0], %1;" ::"l"(out_p), "h"((unsigned short)res) : "memory");
                    if (live && lane == 0 && cta == NS - 1) *(volatile unsigned int*)&g_epoch = tag;
                    if (lane == 0) TL_STAMP(7);
                    CK_STAMP(11);
                }
            }
        }
        TL_FLUSH();
    } else {
        const int qd = cta - NS;
        if (warp == 8) {
            if (lane == 0) {
                for (int s = 0; s < NWO; s++) {
                    mbar_init(bar_full + 8 * s, 1);
                    mbar_init(bar_empty + 8 * s, 8);
                }
                asm volatile("fence.mbarrier_init.release.cluster;" ::: "memory");
            }
            __syncwarp();
            asm volatile("bar.arrive 1, 288;" ::: "memory");
            uint64_t pol;
            asm volatile("createpolicy.fractional.L2::evict_first.b64 %0, 1.0;" : "=l"(pol));
            int slot = 0;
            uint32_t ph = 0;
            for (int h = 0; h < NH; h++) {
                if (lane == 0) {
                    if (h >= NWO) mbar_wait(bar_empty + 8 * slot, ph ^ 1);
                    mbar_expect_tx(bar_full + 8 * slot, 48 * DM * 2);
                }
                __syncwarp();
                const __nv_bfloat16* src = p.wo + (size_t)(h * DH + qd * 48) * DM;
                bulk_load(sb + slot * WO_BUF + lane * WO_PITCH, src + lane * DM, DM * 2, bar_full + 8 * slot, pol);
                if (lane < 16)
                    bulk_load(sb + slot * WO_BUF + (32 + lane) * WO_PITCH, src + (32 + lane) * DM, DM * 2,
                              bar_full + 8 * slot, pol);
                if (++slot == NWO) { slot = 0; ph ^= 1; }
            }
            return;
        }
        if (warp == 9) return;
        if (tid == 255) *tag_s = *(volatile unsigned int*)&g_epoch + 1;
        bar_sync(1, 288);
        const uint32_t tag = *tag_s;
        float acc[5][4];
#pragma unroll
        for (int t = 0; t < 5; t++) acc[t][0] = acc[t][1] = acc[t][2] = acc[t][3] = 0.f;
        const uint32_t a_ow = opaque(sb + SC_OB + warp * 192 + (lane & 15) * 12);
        const uint32_t a_or = opaque(sb + SC_OB + (lane < 24 ? lane : 0) * 8);
        uint4* attn_st = opaque(&g_attn[qd][warp][j == 0 ? g : j == 1 ? 8 + g : 16 + (g >> 1)]);
        const int mi = lane >> 3, r = lane & 7;
        const uint32_t woff = sb + (r + 8 * (mi >> 1)) * WO_PITCH + (80 * warp + 8 * (mi & 1)) * 2;
        const int dc = 2 * warp + (lane >> 4);
        int slot = 0;
        uint32_t ph = 0;
        const uint4* hp0 = &g_phdr[0][lane];
        const uint4* dp0 = &g_pdat[0][qd][dc][lane & 15];
        unsigned int* bell_st = opaque(&g_bell[lane][qd]);
        if (j < 2 || (j == 2 && !(g & 1))) ll_store(attn_st, 0u, 0u, 0u, (tag & 15u) ^ 8u);
        if (warp == 0) st_relaxed(bell_st, 0u);
        for (int h = 0; h < NH; h++) {
            const uint4* hp = opaque(hp0 + h * MAXS);
            const uint4* dp = opaque(dp0 + h * (NCOMB * MAXS * 16));
            uint32_t wf[5][3][4];
            mbar_wait(bar_full + 8 * slot, ph);
#pragma unroll
            for (int t = 0; t < 5; t++)
#pragma unroll
                for (int s = 0; s < 3; s++) ldsm4t(wf[t][s], woff + slot * WO_BUF + s * 16 * WO_PITCH + t * 32);
            __syncwarp();
            if (lane == 0) mbar_arrive(bar_empty + 8 * slot);
            if (++slot == NWO) { slot = 0; ph ^= 1; }

            uint4 hd[4], u[8];
#pragma unroll
            for (int i = 0; i < 4; i++) hd[i] = make_uint4(__float_as_uint(NEG_INF), 0u, 0u, lane + 32 * i < NS ? ~tag : tag);
#pragma unroll
            for (int i = 0; i < 8; i++) u[i] = make_uint4(0u, 0u, 0u, dc + 16 * i < NS ? ~tag : tag);
            uint32_t n = 0;
            if (h < NH - 1) {
                while (true) {
                    bool ok = true;
#pragma unroll
                    for (int i = 0; i < 4; i++)
                        if (hd[i].w != tag) hd[i] = ll_load(hp + 32 * i);
#pragma unroll
                    for (int i = 0; i < 4; i++) ok = ok && (hd[i].w == tag);
                    if (__all_sync(0xffffffffu, ok)) break;
                    if (++n > SPIN_LIMIT) __trap();
                    __nanosleep(1000);
                }
            }
            while (true) {
                bool ok = true;
#pragma unroll
                for (int i = 0; i < 4; i++)
                    if (hd[i].w != tag) hd[i] = ll_load(hp + 32 * i);
#pragma unroll
                for (int i = 0; i < 8; i++)
                    if (u[i].w != tag) u[i] = ll_load(dp + 256 * i);
#pragma unroll
                for (int i = 0; i < 4; i++) ok = ok && (hd[i].w == tag);
#pragma unroll
                for (int i = 0; i < 8; i++) ok = ok && (u[i].w == tag);
                if (__all_sync(0xffffffffu, ok)) break;
                if (++n > SPIN_LIMIT) __trap();
            }
            if (h == NH - 1 && warp == 0) st_relaxed(bell_st, tag);
            if (lane == 0) TL_STAMP(4);
            const float M = warp_max(fmaxf(fmaxf(__uint_as_float(hd[0].x), __uint_as_float(hd[1].x)),
                                           fmaxf(__uint_as_float(hd[2].x), __uint_as_float(hd[3].x))));
            float f[4];
#pragma unroll
            for (int i = 0; i < 4; i++) f[i] = ex2((__uint_as_float(hd[i].x) - M) * LOG2E);
            float L = fmaf(f[0], __uint_as_float(hd[0].y), f[1] * __uint_as_float(hd[1].y)) +
                      fmaf(f[2], __uint_as_float(hd[2].y), f[3] * __uint_as_float(hd[3].y));
            float fa[4], fb[4];
#pragma unroll
            for (int i = 0; i < 4; i++) {
                fa[i] = __shfl_sync(0xffffffffu, f[i], dc);
                fb[i] = __shfl_sync(0xffffffffu, f[i], dc + 16);
            }
            L += __shfl_xor_sync(0xffffffffu, L, 16);
            float o0 = 0.f, o1 = 0.f, o2 = 0.f, o3 = 0.f, o4 = 0.f, o5 = 0.f;
#pragma unroll
            for (int i = 0; i < 4; i++) {
                o0 = fmaf(fa[i], __uint_as_float(u[2 * i].x), o0);
                o1 = fmaf(fa[i], __uint_as_float(u[2 * i].y), o1);
                o2 = fmaf(fa[i], __uint_as_float(u[2 * i].z), o2);
                o3 = fmaf(fb[i], __uint_as_float(u[2 * i + 1].x), o3);
                o4 = fmaf(fb[i], __uint_as_float(u[2 * i + 1].y), o4);
                o5 = fmaf(fb[i], __uint_as_float(u[2 * i + 1].z), o5);
            }
            L += __shfl_xor_sync(0xffffffffu, L, 8);
            o0 += o3;
            o1 += o4;
            o2 += o5;
            o0 += __shfl_xor_sync(0xffffffffu, o0, 16);
            o1 += __shfl_xor_sync(0xffffffffu, o1, 16);
            o2 += __shfl_xor_sync(0xffffffffu, o2, 16);
            L += __shfl_xor_sync(0xffffffffu, L, 4);
            const uint32_t par = (h & 1) * (8 * 192);
            if (lane < 16) {
                sts32(a_ow + par, o0);
                sts32(a_ow + par + 4, o1);
                sts32(a_ow + par + 8, o2);
            }
            bar_sync(2, 256);
            L += __shfl_xor_sync(0xffffffffu, L, 2);
            L += __shfl_xor_sync(0xffffffffu, L, 1);
            const float rL = rcp_fast(L);
            if (lane == 0) TL_STAMP(6);
            float2 ov[8];
#pragma unroll
            for (int w8 = 0; w8 < 8; w8++) ov[w8] = lds64(a_or + par + w8 * 192);
            const float e0 = ((ov[0].x + ov[1].x) + (ov[2].x + ov[3].x)) + ((ov[4].x + ov[5].x) + (ov[6].x + ov[7].x));
            const float e1 = ((ov[0].y + ov[1].y) + (ov[2].y + ov[3].y)) + ((ov[4].y + ov[5].y) + (ov[6].y + ov[7].y));
            const uint32_t pk = pack_bf2(e0 * rL, e1 * rL);
            uint32_t b0[3], b1[3];
#pragma unroll
            for (int s = 0; s < 3; s++) {
                b0[s] = __shfl_sync(0xffffffffu, pk, 8 * s + j);
                b1[s] = __shfl_sync(0xffffffffu, pk, 8 * s + 4 + j);
            }
#pragma unroll
            for (int s = 0; s < 3; s++)
#pragma unroll
                for (int t = 4; t >= 0; t--)
                    mma16816(acc[t], wf[t][s][0], wf[t][s][1], wf[t][s][2], wf[t][s][3], b0[s], b1[s]);
        }
        {
            const float n8 = __shfl_down_sync(0xffffffffu, acc[4][0], 4), n9 = __shfl_down_sync(0xffffffffu, acc[4][2], 4);
            const float v0 = j == 0 ? acc[0][0] : j == 1 ? acc[2][0] : acc[4][0];
            const float v1 = j == 0 ? acc[0][2] : j == 1 ? acc[2][2] : acc[4][2];
            const float v2 = j == 0 ? acc[1][0] : j == 1 ? acc[3][0] : n8;
            const float v3 = j == 0 ? acc[1][2] : j == 1 ? acc[3][2] : n9;
            if (j < 2 || (j == 2 && !(g & 1)))
                ll_store(attn_st, __float_as_uint(v0), __float_as_uint(v1), __float_as_uint(v2),
                         (__float_as_uint(v3) & ~15u) | (tag & 15u));
        }
        if (lane == 0) TL_STAMP(5);
    }
}

}

extern "C" void kernel_launch(void* const* d_in, const int* in_sizes, int n_in, void* d_out, int out_size) {
    using namespace fused;
    static int grid = 0;
    static CUtensorMap tm_wq;
    static const void* tm_ptr = nullptr;
    if (grid == 0) {
        int dev = 0, sms = 0;
        cudaGetDevice(&dev);
        cudaDeviceGetAttribute(&sms, cudaDevAttrMultiProcessorCount, dev);
        cudaFuncSetAttribute(fused_kernel, cudaFuncAttributeMaxDynamicSharedMemorySize, SM_TOTAL);
        grid = sms < MAXS + NCOMB ? sms : MAXS + NCOMB;
    }
    if (tm_ptr != d_in[3]) {
        typedef CUresult (*EncodeFn)(CUtensorMap*, CUtensorMapDataType, cuuint32_t, void*, const cuuint64_t*,
                                     const cuuint64_t*, const cuuint32_t*, const cuuint32_t*, CUtensorMapInterleave,
                                     CUtensorMapSwizzle, CUtensorMapL2promotion, CUtensorMapFloatOOBfill);
        void* fn = nullptr;
        cudaDriverEntryPointQueryResult qr;
        cudaGetDriverEntryPoint("cuTensorMapEncodeTiled", &fn, cudaEnableDefault, &qr);
        cuuint64_t gdim[2] = {(cuuint64_t)HD, (cuuint64_t)DM};
        cuuint64_t gstr[1] = {(cuuint64_t)HD * 2};
        cuuint32_t box[2] = {48, (cuuint32_t)WQ_BOX_ROWS};
        cuuint32_t estr[2] = {1, 1};
        ((EncodeFn)fn)(&tm_wq, CU_TENSOR_MAP_DATA_TYPE_BFLOAT16, 2, d_in[3], gdim, gstr, box, estr,
                       CU_TENSOR_MAP_INTERLEAVE_NONE, CU_TENSOR_MAP_SWIZZLE_NONE, CU_TENSOR_MAP_L2_PROMOTION_L2_128B,
                       CU_TENSOR_MAP_FLOAT_OOB_FILL_NONE);
        tm_ptr = d_in[3];
    }
    Params p;
    p.x = (const __nv_bfloat16*)d_in[0];
    p.k = (const char*)d_in[1];
    p.v = (const char*)d_in[2];
    p.wq = (const __nv_bfloat16*)d_in[3];
    p.wo = (const __nv_bfloat16*)d_in[4];
    p.wg = (const __nv_bfloat16*)d_in[6];
    p.wu = (const __nv_bfloat16*)d_in[7];
    p.wd = (const __nv_bfloat16*)d_in[8];
    p.out = (__nv_bfloat16*)d_out;
    fused_kernel<<<grid, NTHREADS, SM_TOTAL, cudaStreamPerThread>>>(p, tm_wq);
}
```

```cpp
#include <cuda_runtime.h>
#include <cuda.h>
#include <cuda_bf16.h>
#include <stdint.h>

namespace fused {

constexpr int DM = 640;
constexpr int NH = 32;
constexpr int SK = 32768;
constexpr int DH = 192;
constexpr int HD = NH * DH;
constexpr int FF = 1536;
constexpr int ROWB = DH * 2;
constexpr int ITEM_KEYS = 64;
constexpr int CHUNK = ITEM_KEYS * ROWB;
constexpr int ITEMS_PER_HEAD = SK / ITEM_KEYS;
constexpr int NITEMS = NH * ITEMS_PER_HEAD;
constexpr int NSLOT = 6;
constexpr int NPRE = NSLOT / 2;
constexpr int NCOMB = 4;
constexpr int MAXS = 128;
constexpr int NGU = FF / 16;
constexpr int NDN = DM / 8;
constexpr int DELAY_GU = 1000;
constexpr int DELAY_D = 3000;
constexpr int NQS = HD / 48;
constexpr int WQ_BOX_ROWS = 160;
constexpr int NTHREADS = 320;

constexpr int SM_RING = 0;
constexpr int SM_WG = NSLOT * CHUNK;
constexpr int SM_WU = SM_WG + DM * 32;
constexpr int SM_WD = SM_WU + DM * 32;
constexpr int SM_Q = SM_WD + FF * 16;
constexpr int SM_OBUF = SM_Q + HD * 2;
constexpr int SM_ML = SM_OBUF + 2 * 4 * DH * 4;
constexpr int SM_BAR = SM_ML + 160;
constexpr int SM_META = SM_BAR + 20 * 8;
constexpr int SM_TAG = SM_META + 16;
constexpr int SM_TOTAL = SM_TAG + 16;
constexpr int SM_XS = SM_Q;
constexpr int SM_XN = SM_Q + DM * 4;
constexpr int SM_QRED = SM_XN + DM * 2;
constexpr int SM_WQ = SM_WG;
constexpr int SM_H = 0;
constexpr int SM_RED = DM * 4;
constexpr int SM_RED2 = SM_RED + 8 * 64 * 4;
constexpr int SM_ST = SM_RED2 + 8 * 8 * 4;
constexpr int WO_PITCH = DM * 2 + 16;
constexpr int WO_BUF = 48 * WO_PITCH;
constexpr int NWO = 3;
constexpr int SC_OB = NWO * WO_BUF;
static_assert(SC_OB + 2 * 8 * 48 * 4 <= SM_BAR, "combine smem overlaps barriers");
static_assert(SM_TOTAL <= 232448, "smem");

constexpr float LOG2E = 1.4426950408889634f;
constexpr float QK_SCALE = 0.07216878364870322f;
constexpr float NEG_INF = -__builtin_huge_valf();

__device__ unsigned int g_epoch;
__device__ unsigned int g_work;
__device__ unsigned int g_exit;
__device__ uint4 g_q[HD / 6];
__device__ uint4 g_phdr[NH][MAXS];
__device__ uint4 g_pdat[NH][NCOMB][MAXS][16];
__device__ uint4 g_attn[NCOMB][8][32];
__device__ uint4 g_act[NGU][4];
__device__ unsigned int g_bell[32][32];

__device__ __forceinline__ uint32_t s2u(const void* p) { return (uint32_t)__cvta_generic_to_shared(p); }
__device__ __forceinline__ uint32_t pack_bf2(float lo, float hi) {
    uint32_t r;
    asm("cvt.rn.bf16x2.f32 %0, %1, %2;" : "=r"(r) : "f"(hi), "f"(lo));
    return r;
}
__device__ __forceinline__ float bfr(float x) { return __uint_as_float(pack_bf2(0.f, x)); }
template <typename T>
__device__ __forceinline__ T* opaque(T* p) {
    asm volatile("" : "+l"(p));
    return p;
}
__device__ __forceinline__ uint32_t opaque(uint32_t v) {
    asm volatile("" : "+r"(v));
    return v;
}
__device__ __forceinline__ float4 lds128(uint32_t a) {
    float4 v;
    asm volatile("ld.shared.v4.f32 {%0,%1,%2,%3}, [%4];" : "=f"(v.x), "=f"(v.y), "=f"(v.z), "=f"(v.w) : "r"(a) : "memory");
    return v;
}
__device__ __forceinline__ float2 lds64(uint32_t a) {
    float2 v;
    asm volatile("ld.shared.v2.f32 {%0,%1}, [%2];" : "=f"(v.x), "=f"(v.y) : "r"(a) : "memory");
    return v;
}
__device__ __forceinline__ float lds32(uint32_t a) {
    float v;
    asm volatile("ld.shared.f32 %0, [%1];" : "=f"(v) : "r"(a) : "memory");
    return v;
}
__device__ __forceinline__ void sts128(uint32_t a, float x, float y, float z, float w) {
    asm volatile("st.shared.v4.f32 [%0], {%1,%2,%3,%4};" ::"r"(a), "f"(x), "f"(y), "f"(z), "f"(w) : "memory");
}
__device__ __forceinline__ void sts64(uint32_t a, float x, float y) {
    asm volatile("st.shared.v2.f32 [%0], {%1,%2};" ::"r"(a), "f"(x), "f"(y) : "memory");
}
__device__ __forceinline__ void sts32(uint32_t a, float x) {
    asm volatile("st.shared.f32 [%0], %1;" ::"r"(a), "f"(x) : "memory");
}
__device__ __forceinline__ float bf_lo(uint32_t v) { return __uint_as_float(v << 16); }
__device__ __forceinline__ float bf_hi(uint32_t v) { return __uint_as_float(v & 0xffff0000u); }
__device__ __forceinline__ float ex2(float x) {
    float r;
    asm("ex2.approx.ftz.f32 %0, %1;" : "=f"(r) : "f"(x));
    return r;
}
__device__ __forceinline__ float rcp_fast(float x) {
    float r;
    asm("rcp.approx.ftz.f32 %0, %1;" : "=f"(r) : "f"(x));
    return r;
}
__device__ __forceinline__ float sqrt_fast(float x) {
    float r;
    asm("sqrt.approx.ftz.f32 %0, %1;" : "=f"(r) : "f"(x));
    return r;
}
__device__ __forceinline__ uint32_t ld_relaxed(const unsigned int* p) {
    uint32_t v;
    asm volatile("ld.relaxed.gpu.global.u32 %0, [%1];" : "=r"(v) : "l"(p) : "memory");
    return v;
}
__device__ __forceinline__ void st_relaxed(unsigned int* p, uint32_t v) {
    asm volatile("st.relaxed.gpu.global.u32 [%0], %1;" ::"l"(p), "r"(v) : "memory");
}
__device__ __forceinline__ void mbar_init(uint32_t bar, uint32_t cnt) {
    asm volatile("mbarrier.init.shared.b64 [%0], %1;" ::"r"(bar), "r"(cnt) : "memory");
}
__device__ __forceinline__ void mbar_expect_tx(uint32_t bar, uint32_t bytes) {
    asm volatile("mbarrier.arrive.expect_tx.shared.b64 _, [%0], %1;" ::"r"(bar), "r"(bytes) : "memory");
}
__device__ __forceinline__ void mbar_arrive(uint32_t bar) {
    asm volatile("mbarrier.arrive.shared.b64 _, [%0];" ::"r"(bar) : "memory");
}
__device__ __forceinline__ bool mbar_try(uint32_t bar, uint32_t parity) {
    uint32_t ok;
    asm volatile(
        "{\n .reg .pred p;\n mbarrier.try_wait.parity.shared.b64 p, [%1], %2;\n selp.u32 %0, 1, 0, p;\n}"
        : "=r"(ok)
        : "r"(bar), "r"(parity)
        : "memory");
    return ok != 0;
}
constexpr uint32_t SPIN_LIMIT = 1u << 24;
__device__ __forceinline__ void mbar_wait(uint32_t bar, uint32_t parity) {
    uint32_t n = 0;
    while (!mbar_try(bar, parity)) {
        if (++n > SPIN_LIMIT) __trap();
    }
}
__device__ __forceinline__ void bulk_load(uint32_t dst, const void* src, uint32_t bytes, uint32_t bar, uint64_t pol) {
    asm volatile(
        "cp.async.bulk.shared::cluster.global.mbarrier::complete_tx::bytes.L2::cache_hint [%0], [%1], %2, [%3], %4;"
        ::"r"(dst), "l"(src), "r"(bytes), "r"(bar), "l"(pol)
        : "memory");
}
__device__ __forceinline__ void tma_load_2d(uint32_t dst, const CUtensorMap* tm, int c0, int c1, uint32_t bar) {
    asm volatile(
        "cp.async.bulk.tensor.2d.shared::cluster.global.mbarrier::complete_tx::bytes [%0], [%1, {%3, %4}], [%2];"
        ::"r"(dst), "l"(tm), "r"(bar), "r"(c0), "r"(c1)
        : "memory");
}
__device__ __forceinline__ void ll_store(uint4* p, uint32_t a, uint32_t b, uint32_t c, uint32_t tag) {
    asm volatile(
        "{\n .reg .b128 t;\n .reg .b64 lo, hi;\n mov.b64 lo, {%1, %2};\n mov.b64 hi, {%3, %4};\n"
        " mov.b128 t, {lo, hi};\n st.relaxed.gpu.global.b128 [%0], t;\n}"
        ::"l"(p), "r"(a), "r"(b), "r"(c), "r"(tag)
        : "memory");
}
__device__ __forceinline__ uint4 ll_load(const uint4* p) {
    uint4 v;
    asm volatile(
        "{\n .reg .b128 t;\n .reg .b64 lo, hi;\n ld.relaxed.gpu.global.b128 t, [%4];\n"
        " mov.b128 {lo, hi}, t;\n mov.b64 {%0, %1}, lo;\n mov.b64 {%2, %3}, hi;\n}"
        : "=r"(v.x), "=r"(v.y), "=r"(v.z), "=r"(v.w)
        : "l"(p)
        : "memory");
    return v;
}
__device__ __forceinline__ void ldsm4(uint32_t (&r)[4], uint32_t addr) {
    asm volatile("ldmatrix.sync.aligned.m8n8.x4.shared.b16 {%0,%1,%2,%3}, [%4];"
                 : "=r"(r[0]), "=r"(r[1]), "=r"(r[2]), "=r"(r[3])
                 : "r"(addr)
                 : "memory");
}
__device__ __forceinline__ void ldsm4t(uint32_t (&r)[4], uint32_t addr) {
    asm volatile("ldmatrix.sync.aligned.m8n8.x4.trans.shared.b16 {%0,%1,%2,%3}, [%4];"
                 : "=r"(r[0]), "=r"(r[1]), "=r"(r[2]), "=r"(r[3])
                 : "r"(addr)
                 : "memory");
}
__device__ __forceinline__ void mma16816(float (&c)[4], uint32_t a0, uint32_t a1, uint32_t a2, uint32_t a3,
                                         uint32_t b0, uint32_t b1) {
    asm volatile(
        "mma.sync.aligned.m16n8k16.row.col.f32.bf16.bf16.f32 {%0,%1,%2,%3}, {%4,%5,%6,%7}, {%8,%9}, {%0,%1,%2,%3};"
        : "+f"(c[0]), "+f"(c[1]), "+f"(c[2]), "+f"(c[3])
        : "r"(a0), "r"(a1), "r"(a2), "r"(a3), "r"(b0), "r"(b1));
}
__device__ __forceinline__ void bar_sync(int id, int n) {
    __syncwarp();
    asm volatile("bar.sync %0, %1;" ::"r"(id), "r"(n) : "memory");
}
__device__ __forceinline__ void delay_cycles(uint32_t c) {
    uint32_t t0, t1;
    asm volatile("mov.u32 %0, %clock;" : "=r"(t0)::"memory");
    do {
        asm volatile("mov.u32 %0, %clock;" : "=r"(t1)::"memory");
    } while (t1 - t0 < c);
}
__device__ __forceinline__ float warp_max(float v) {
    int k = __float_as_int(v);
    k ^= (k >> 31) & 0x7fffffff;
    k = __reduce_max_sync(0xffffffffu, k);
    k ^= (k >> 31) & 0x7fffffff;
    return __int_as_float(k);
}

__device__ __forceinline__ void ln_stats(const float* v, int lane, float& mean_b, float& sd_b) {
    const float4* v4 = reinterpret_cast<const float4*>(v);
    float piv = v[0];
    float s1 = 0.f, s2 = 0.f;
#pragma unroll
    for (int i = 0; i < 5; i++) {
        float4 a = v4[lane + 32 * i];
        float d0 = a.x - piv, d1 = a.y - piv, d2 = a.z - piv, d3 = a.w - piv;
        s1 += (d0 + d1) + (d2 + d3);
        s2 += (d0 * d0 + d1 * d1) + (d2 * d2 + d3 * d3);
    }
#pragma unroll
    for (int o = 16; o > 0; o >>= 1) {
        s1 += __shfl_xor_sync(0xffffffffu, s1, o);
        s2 += __shfl_xor_sync(0xffffffffu, s2, o);
    }
    float md = s1 * (1.0f / DM);
    float var = fmaxf(s2 * (1.0f / DM) - md * md, 0.f);
    mean_b = bfr(piv + md);
    sd_b = bfr(__fsqrt_rn(bfr(bfr(var) + 1e-5f)));
}
__device__ __forceinline__ float ln_apply(float x, float mean_b, float sd_b) {
    return bfr(__fdiv_rn(bfr(x - mean_b), sd_b));
}

struct Params {
    const __nv_bfloat16* x;
    const char* k;
    const char* v;
    const __nv_bfloat16* wo;
    __nv_bfloat16* out;
};

__global__ void __launch_bounds__(NTHREADS, 1)
fused_kernel(const Params p, const __grid_constant__ CUtensorMap tm_wq, const __grid_constant__ CUtensorMap tm_wg,
             const __grid_constant__ CUtensorMap tm_wu, const __grid_constant__ CUtensorMap tm_wd) {
    extern __shared__ __align__(1024) unsigned char smem[];
    const uint32_t sb = opaque(s2u(smem));
    const int tid = threadIdx.x, warp = tid >> 5, lane = tid & 31;
    const int g = lane >> 2, j = lane & 3;
    const int NS = gridDim.x - NCOMB;
    const int cta = blockIdx.x;
    const uint32_t bar_full = sb + SM_BAR, bar_empty = sb + SM_BAR + 8 * NSLOT, bar_wq = sb + SM_BAR + 16 * NSLOT;
    const uint32_t bar_q = bar_wq + 16, bar_w = bar_q + 8;
    volatile int* meta = reinterpret_cast<volatile int*>(smem + SM_META);
    volatile uint32_t* tag_s = reinterpret_cast<volatile uint32_t*>(smem + SM_TAG);

    if (tid == 256 && cta < NS) {
        asm volatile("cp.async.bulk.prefetch.L2.global [%0], %1;" ::"l"(p.k + (size_t)cta * CHUNK), "r"(CHUNK / 4) : "memory");
        mbar_init(bar_wq, 1);
        mbar_init(bar_wq + 8, 1);
        asm volatile("fence.mbarrier_init.release.cluster;" ::: "memory");
#pragma unroll
        for (int i = 0; i < 4; i++) {
            if (!(i & 1)) mbar_expect_tx(bar_wq + 4 * i, DM * 48);
            tma_load_2d(sb + SM_WQ + i * WQ_BOX_ROWS * 96, &tm_wq, cta * 48, i * WQ_BOX_ROWS, bar_wq + 8 * (i >> 1));
        }
    }

    if (cta < NS) {
        if (warp == 8) {
            if (lane == 0) {
                for (int s = 0; s < NSLOT; s++) {
                    mbar_init(bar_full + 8 * s, 1);
                    mbar_init(bar_empty + 8 * s, 4);
                }
                mbar_init(bar_q, 4);
                for (int i = 0; i < 2; i++) mbar_init(bar_w + 8 * i, 1);
                meta[3] = 0;
                asm volatile("fence.mbarrier_init.release.cluster;" ::: "memory");
            }
            __syncwarp();
            asm volatile("bar.arrive 1, 320;" ::: "memory");
            if (lane == 0) {
                uint64_t pol;
                asm volatile("createpolicy.fractional.L2::evict_first.b64 %0, 1.0;" : "=l"(pol));
#pragma unroll
                for (int c = 0; c < NSLOT; c++) {
                    mbar_wait(c < 2 ? bar_wq + 8 * c : bar_full + 8 * (c - 2), 0);
                    const int item = cta + NS * (c >> 1);
                    if (!(c & 1)) meta[c >> 1] = item;
                    mbar_expect_tx(bar_full + 8 * c, CHUNK);
                    bulk_load(sb + SM_RING + c * CHUNK, ((c & 1) ? p.v : p.k) + (size_t)item * CHUNK, CHUNK,
                              bar_full + 8 * c, pol);
                }
                int slot = 0;
                uint32_t ph = 1;
                int lslot = NSLOT - 2;
                uint32_t lph = 0;
                while (true) {
                    mbar_wait(bar_full + 8 * lslot, lph);
                    mbar_wait(bar_empty + 8 * slot, ph ^ 1);
                    const int item = NS * NPRE + (int)atomicAdd(&g_work, 1u);
                    if (item >= NITEMS) break;
                    meta[slot >> 1] = item;
                    mbar_expect_tx(bar_full + 8 * slot, CHUNK);
                    bulk_load(sb + SM_RING + slot * CHUNK, p.k + (size_t)item * CHUNK, CHUNK, bar_full + 8 * slot, pol);
                    mbar_wait(bar_empty + 8 * slot + 8, ph ^ 1);
                    mbar_expect_tx(bar_full + 8 * slot + 8, CHUNK);
                    bulk_load(sb + SM_RING + (slot + 1) * CHUNK, p.v + (size_t)item * CHUNK, CHUNK, bar_full + 8 * slot + 8, pol);
                    lslot = slot;
                    lph = ph;
                    slot += 2;
                    if (slot == NSLOT) { slot = 0; ph ^= 1; }
                }
                meta[slot >> 1] = -1;
                meta[3] = 1;
                mbar_arrive(bar_full + 8 * slot);
                unsigned int e = atomicAdd(&g_exit, 1u);
                if (e == (unsigned)NS - 1) {
                    *(volatile unsigned int*)&g_work = 0;
                    *(volatile unsigned int*)&g_exit = 0;
                }
            }
            return;
        }
        float* xs = reinterpret_cast<float*>(smem + SM_XS);
        const int dn_idx = cta - (NS - NDN);
        if (warp == 9) {
            uint2 xv[5];
#pragma unroll
            for (int i = 0; i < 5; i++) xv[i] = *reinterpret_cast<const uint2*>(p.x + 4 * (lane + 32 * i));
            if (lane == 0) *tag_s = *(volatile unsigned int*)&g_epoch + 1;
#pragma unroll
            for (int i = 0; i < 5; i++)
                *reinterpret_cast<float4*>(xs + 4 * (lane + 32 * i)) =
                    make_float4(bf_lo(xv[i].x), bf_hi(xv[i].x), bf_lo(xv[i].y), bf_hi(xv[i].y));
            __syncwarp();
            float mean_b, sd_b;
            ln_stats(xs, lane, mean_b, sd_b);
#pragma unroll
            for (int i = 0; i < 5; i++)
                *reinterpret_cast<uint2*>(smem + SM_XN + 8 * (lane + 32 * i)) =
                    make_uint2(pack_bf2(ln_apply(bf_lo(xv[i].x), mean_b, sd_b), ln_apply(bf_hi(xv[i].x), mean_b, sd_b)),
                               pack_bf2(ln_apply(bf_lo(xv[i].y), mean_b, sd_b), ln_apply(bf_hi(xv[i].y), mean_b, sd_b)));
            bar_sync(1, 320);
            if (lane == 0) {
                mbar_wait(bar_q, 0);
                asm volatile("fence.proxy.async.shared::cta;" ::: "memory");
                bool warm = false;
                for (uint32_t n = 0; meta[3] == 0; n++) {
                    const int left = NITEMS - NS * NPRE - (int)ld_relaxed(&g_work);
                    if (left <= 0) break;
                    if (left < 512 && !warm) {
                        asm volatile("prefetch.tensormap [%0];" ::"l"(&tm_wg) : "memory");
                        asm volatile("prefetch.tensormap [%0];" ::"l"(&tm_wu) : "memory");
                        asm volatile("prefetch.tensormap [%0];" ::"l"(&tm_wd) : "memory");
                        warm = true;
                    }
                    for (int i = left / 256; i > 0 && meta[3] == 0; i--) __nanosleep(1000);
                    __nanosleep(100);
                    if (n > SPIN_LIMIT) __trap();
                }
                delay_cycles(DELAY_GU);
                if (cta < NGU) {
                    mbar_expect_tx(bar_w, DM * 64);
                    for (int i = 0; i < 4; i++) {
                        tma_load_2d(sb + SM_WG + i * 5120, &tm_wg, cta * 16, i * 160, bar_w);
                        tma_load_2d(sb + SM_WU + i * 5120, &tm_wu, cta * 16, i * 160, bar_w);
                    }
                }
                if (dn_idx >= 0) {
                    delay_cycles(DELAY_D);
                    mbar_expect_tx(bar_w + 8, FF * 16);
                    for (int i = 0; i < 6; i++) tma_load_2d(sb + SM_WD + i * 4096, &tm_wd, dn_idx * 8, i * 256, bar_w + 8);
                }
            }
            return;
        }
        float* qred = reinterpret_cast<float*>(smem + SM_QRED);
        if (tid < 8)
            for (int slice = cta; slice < NQS; slice += NS) ll_store(&g_q[slice * 8 + tid], 0u, 0u, 0u, 0u);
        if (warp == 4 && lane < 8 && !(lane & 1) && cta < NGU) ll_store(&g_act[cta][lane >> 1], 0u, 0u, 0u, 0u);
        bar_sync(1, 320);
        const uint32_t tag = *tag_s;
        for (int slice = cta, it = 0; slice < NQS; slice += NS, it++) {
            if (it > 0) {
                bar_sync(2, 256);
                if (tid == 0) {
                    mbar_expect_tx(bar_wq, DM * 48);
                    mbar_expect_tx(bar_wq + 8, DM * 48);
                    for (int i = 0; i < DM / WQ_BOX_ROWS; i++)
                        tma_load_2d(sb + SM_WQ + i * WQ_BOX_ROWS * 96, &tm_wq, slice * 48, i * WQ_BOX_ROWS, bar_wq + 8 * (i >> 1));
                }
            }
            const uint32_t* xn = reinterpret_cast<const uint32_t*>(smem + SM_XN) + 40 * warp + j;
            const uint32_t wa = sb + SM_WQ + (80 * warp + (lane & 7) + 8 * (lane >> 4)) * 96 + ((lane >> 3) & 1) * 16;
            float c[3][4];
#pragma unroll
            for (int t = 0; t < 3; t++) c[t][0] = c[t][1] = c[t][2] = c[t][3] = 0.f;
            mbar_wait(bar_wq + 8 * (warp >> 2), it & 1);
#pragma unroll
            for (int s = 0; s < 5; s++) {
                const uint32_t b0 = xn[8 * s], b1 = xn[8 * s + 4];
#pragma unroll
                for (int t = 0; t < 3; t++) {
                    uint32_t a[4];
                    ldsm4t(a, wa + s * 16 * 96 + t * 32);
                    mma16816(c[t], a[0], a[1], a[2], a[3], b0, b1);
                }
            }
            if (j < 3) {
                qred[warp * 48 + 16 * j + g] = j == 0 ? c[0][0] : j == 1 ? c[1][0] : c[2][0];
                qred[warp * 48 + 16 * j + g + 8] = j == 0 ? c[0][2] : j == 1 ? c[1][2] : c[2][2];
            }
            bar_sync(2, 256);
            if (warp == 0) {
                float2 s = make_float2(0.f, 0.f);
                const int pi = lane < 24 ? lane : 0;
#pragma unroll
                for (int w8 = 0; w8 < 8; w8++) {
                    float2 v = *reinterpret_cast<const float2*>(qred + w8 * 48 + 2 * pi);
                    s.x += v.x;
                    s.y += v.y;
                }
                const uint32_t pk = pack_bf2(s.x, s.y);
                const uint32_t p0 = __shfl_sync(0xffffffffu, pk, 3 * (lane & 7));
                const uint32_t p1 = __shfl_sync(0xffffffffu, pk, 3 * (lane & 7) + 1);
                const uint32_t p2 = __shfl_sync(0xffffffffu, pk, 3 * (lane & 7) + 2);
                if (lane < 8) ll_store(&g_q[slice * 8 + lane], p0, p1, p2, tag);
            }
        }
        bar_sync(2, 256);
        {
            uint32_t* qs = reinterpret_cast<uint32_t*>(smem + SM_Q);
            uint32_t n = 0;
            if (warp == 0) {
                uint4 u;
                while ((u = ll_load(&g_q[lane])).w != tag) {
                    if (++n > SPIN_LIMIT) __trap();
                }
                qs[3 * lane] = u.x;
                qs[3 * lane + 1] = u.y;
                qs[3 * lane + 2] = u.z;
            } else if (warp >= 4) {
                uint4 u[8];
#pragma unroll
                for (int i = 0; i < 8; i++) u[i].w = 0u;
                while (true) {
                    bool ok = true;
#pragma unroll
                    for (int i = 0; i < 8; i++)
                        if (u[i].w != tag) u[i] = ll_load(&g_q[tid - 128 + 128 * i]);
#pragma unroll
                    for (int i = 0; i < 8; i++) ok = ok && (u[i].w == tag);
                    if (ok) break;
                    if (++n > SPIN_LIMIT) __trap();
                    __nanosleep(200);
                }
#pragma unroll
                for (int i = 0; i < 8; i++) {
                    const int un = tid - 128 + 128 * i;
                    if (un >= 32) {
                        qs[3 * un] = u[i].x;
                        qs[3 * un + 1] = u[i].y;
                        qs[3 * un + 2] = u[i].z;
                    }
                }
                __syncwarp();
                if (lane == 0) mbar_arrive(bar_q);
            }
            if (warp < 4) bar_sync(3, 128);
        }

        if (warp < 4) {
            const int mi = lane >> 3, r = lane & 7;
            uint32_t offK[4], offV[4];
            {
                int keyK = 16 * warp + r + 8 * (mi & 1), zK = (mi >> 1) ^ r;
                int keyV = 16 * warp + r + 8 * (mi >> 1), zV = (mi & 1) ^ r;
#pragma unroll
                for (int u = 0; u < 4; u++) {
                    offK[u] = sb + SM_RING + keyK * ROWB + (((2 * u) ^ zK) << 4);
                    offV[u] = sb + SM_RING + keyV * ROWB + (((2 * u) ^ zV) << 4);
                }
            }
            const bool valid = (j == (g >> 1));
            const bool odd = g & 1;
            float acc[12][4];
#pragma unroll
            for (int t = 0; t < 12; t++) acc[t][0] = acc[t][1] = acc[t][2] = acc[t][3] = 0.f;
            float m_run = NEG_INF, r_run = NEG_INF, fr_run = 0.f, l_run = 0.f;
            uint32_t qf[12][2];
            int cur = -1;
            int pub = 0;
            int slot = 0;
            uint32_t ph = 0;
            uint4* pub_p = tid < 64 ? &g_pdat[0][tid >> 4][cta][tid & 15] : &g_phdr[0][cta];
            const int pub_step = tid < 64 ? NCOMB * MAXS * 16 : MAXS;
            const uint32_t a_ow = sb + SM_OBUF + (warp * DH + 16 * j + g) * 4;
            const uint32_t a_or = sb + SM_OBUF + (tid < 64 ? 12 * tid : 0);
            const uint32_t* qs = reinterpret_cast<const uint32_t*>(smem + SM_Q);

            while (true) {
                mbar_wait(bar_full + 8 * slot, ph);
                const int item = meta[slot >> 1];
                const int head = item < 0 ? NH : item / ITEMS_PER_HEAD;
                if (head != cur) {
                    while (pub < head) {
                        const uint32_t par = pub & 1;
                        pub_p = opaque(pub_p);
                        float l = l_run;
                        l += __shfl_xor_sync(0xffffffffu, l, 16);
                        float w0[6], w2[6];
#pragma unroll
                        for (int T = 0; T < 3; T++) {
#pragma unroll
                            for (int b = 0; b < 2; b++) {
                                float v0 = b ? acc[4 * T + 0][1] + acc[4 * T + 0][2] : acc[4 * T + 0][0] + acc[4 * T + 0][3];
                                float v1 = b ? acc[4 * T + 1][1] + acc[4 * T + 1][2] : acc[4 * T + 1][0] + acc[4 * T + 1][3];
                                float v2 = b ? acc[4 * T + 2][1] + acc[4 * T + 2][2] : acc[4 * T + 2][0] + acc[4 * T + 2][3];
                                float v3 = b ? acc[4 * T + 3][1] + acc[4 * T + 3][2] : acc[4 * T + 3][0] + acc[4 * T + 3][3];
                                w0[2 * T + b] = v0 + __shfl_xor_sync(0xffffffffu, v1, 1);
                                w2[2 * T + b] = v2 + __shfl_xor_sync(0xffffffffu, v3, 1);
                            }
                        }
                        l += __shfl_xor_sync(0xffffffffu, l, 8);
#pragma unroll
                        for (int i = 0; i < 6; i++) w0[i] += __shfl_xor_sync(0xffffffffu, w2[i], 2);
                        l += __shfl_xor_sync(0xffffffffu, l, 4);
#pragma unroll
                        for (int i = 0; i < 6; i++) sts32(a_ow + par * (4 * DH * 4) + ((i >> 1) * 64 + (i & 1) * 8) * 4, w0[i]);
                        if (lane < 4) sts32(sb + SM_ML + par * 80 + 16 + warp * 16 + lane * 4, l);
                        if (lane == 0) sts32(sb + SM_ML + par * 80 + warp * 4, r_run);
                        bar_sync(3, 128);
                        if (tid <= 64) {
                            const float4 m4 = lds128(sb + SM_ML + par * 80);
                            float ov[4][3];
                            float4 l4[4];
#pragma unroll
                            for (int w4 = 0; w4 < 4; w4++) {
                                if (tid < 64) {
#pragma unroll
                                    for (int e = 0; e < 3; e++) ov[w4][e] = lds32(a_or + par * (4 * DH * 4) + (w4 * DH + e) * 4);
                                } else {
                                    l4[w4] = lds128(sb + SM_ML + par * 80 + 16 + w4 * 16);
                                    ov[w4][0] = 0.f;
                                    ov[w4][1] = (l4[w4].x + l4[w4].y) + (l4[w4].z + l4[w4].w);
                                    ov[w4][2] = 0.f;
                                }
                            }
                            const float M = fmaxf(fmaxf(m4.x, m4.y), fmaxf(m4.z, m4.w));
                            const float Ms = M == NEG_INF ? 0.f : M;
                            const float f0 = ex2(m4.x - Ms), f1 = ex2(m4.y - Ms), f2 = ex2(m4.z - Ms), f3 = ex2(m4.w - Ms);
                            float r3[3];
#pragma unroll
                            for (int e = 0; e < 3; e++)
                                r3[e] = fmaf(f0, ov[0][e], f1 * ov[1][e]) + fmaf(f2, ov[2][e], f3 * ov[3][e]);
                            ll_store(pub_p, __float_as_uint(tid < 64 ? r3[0] : M), __float_as_uint(r3[1]),
                                     __float_as_uint(r3[2]), tag);
                        }
                        pub_p += pub_step;
#pragma unroll
                        for (int t = 0; t < 12; t++) acc[t][0] = acc[t][1] = acc[t][2] = acc[t][3] = 0.f;
                        m_run = r_run = NEG_INF;
                        l_run = 0.f;
                        pub++;
                    }
                    if (item < 0) break;
                    if (head > 0) mbar_wait(bar_q, 0);
                    cur = head;
                    const uint32_t* qh = qs + head * (DH / 2) + j;
#pragma unroll
                    for (int t = 0; t < 12; t++) {
                        qf[t][0] = qh[((t >> 2) * 8 + ((2 * (t & 3)) ^ g)) * 4];
                        qf[t][1] = qh[((t >> 2) * 8 + ((2 * (t & 3) + 1) ^ g)) * 4];
                    }
                }
                const uint32_t so = slot * CHUNK;
                float s0[4] = {0.f, 0.f, 0.f, 0.f}, s1[4] = {0.f, 0.f, 0.f, 0.f};
#pragma unroll
                for (int t = 0; t < 12; t += 2) {
                    uint32_t a[4], b[4];
                    ldsm4(a, offK[t & 3] + so + (t >> 2) * 128);
                    ldsm4(b, offK[(t + 1) & 3] + so + ((t + 1) >> 2) * 128);
                    mma16816(s0, a[0], a[1], a[2], a[3], qf[t][0], qf[t][1]);
                    mma16816(s1, b[0], b[1], b[2], b[3], qf[t + 1][0], qf[t + 1][1]);
                }
                __syncwarp();
                if (lane == 0) mbar_arrive(bar_empty + 8 * slot);
                float sa = odd ? s0[1] + s1[1] : s0[0] + s1[0];
                float sb2 = odd ? s0[3] + s1[3] : s0[2] + s1[2];
                sa = valid ? bfr(bfr(sa) * QK_SCALE) : NEG_INF;
                sb2 = valid ? bfr(bfr(sb2) * QK_SCALE) : NEG_INF;
                const float mx = warp_max(fmaxf(sa, sb2));
                if (mx > m_run) {
                    const float x2 = mx * LOG2E, r2 = ceilf(x2);
                    const float al = ex2(r_run - r2);
                    r_run = r2;
                    fr_run = r2 - x2;
#pragma unroll
                    for (int t = 0; t < 12; t++) {
                        acc[t][0] *= al;
                        acc[t][1] *= al;
                        acc[t][2] *= al;
                        acc[t][3] *= al;
                    }
                    l_run *= al;
                    m_run = mx;
                }
                const float pa = ex2(fmaf(sa - m_run, LOG2E, -fr_run)), pb = ex2(fmaf(sb2 - m_run, LOG2E, -fr_run));
                uint32_t b0 = 0, b1 = 0;
                if (valid) {
                    const float ha = bfr(pa), hb = bfr(pb);
                    l_run += ha + hb;
                    b0 = odd ? __float_as_uint(ha) : __float_as_uint(ha) >> 16;
                    b1 = odd ? __float_as_uint(hb) : __float_as_uint(hb) >> 16;
                }
                mbar_wait(bar_full + 8 * (slot + 1), ph);
#pragma unroll
                for (int t = 0; t < 12; t++) {
                    uint32_t a[4];
                    ldsm4t(a, offV[t & 3] + so + CHUNK + (t >> 2) * 128);
                    mma16816(acc[t], a[0], a[1], a[2], a[3], b0, b1);
                }
                __syncwarp();
                if (lane == 0) mbar_arrive(bar_empty + 8 * (slot + 1));
                slot += 2;
                if (slot == NSLOT) { slot = 0; ph ^= 1; }
            }
        }
        {
            bar_sync(2, 256);
            uint32_t wgf[5][4], wuf[5][4], wdf[6][4];
            const bool gu = cta < NGU;
            auto ucol = [](int U, int e) { return U < 16 ? 8 * (4 * (U >> 3) + e) + (U & 7) : 8 * (8 + (e & 1)) + 2 * (U - 16) + (e >> 1); };
            const int mi = lane >> 3, r = lane & 7;
            const int U = lane < 20 ? lane : 0;
            const uint4* attn_p = opaque(&g_attn[0][warp][U]);
            uint4* act_st = opaque(&g_act[gu ? cta : 0][(lane >> 1) & 3]);
            const uint4* act_p0 = opaque(&g_act[12 * warp + g][j]);
            const uint4* act_p1 = opaque(&g_act[12 * warp + 8 + (g & 3)][j]);
            __nv_bfloat16* out_p = opaque(p.out + (dn_idx >= 0 ? dn_idx * 8 : 0) + (lane & 7));
            const unsigned int* bell_p = opaque(&g_bell[(cta * 8 + warp) & 31][j]);
            const uint32_t a_h = opaque(sb + SM_H + (80 * warp + ucol(U, 0)) * 4);
            const uint32_t a_h2 = opaque(a_h + (U < 16 ? 64 : 4));
            const uint32_t a_st = opaque(sb + SM_ST + warp * 16);
            const uint32_t a_red = opaque(sb + SM_RED + warp * 256 + (g + 8 * j) * 8);
            const uint32_t a_fin = opaque(sb + SM_RED + (lane & 7) * 16);
            const uint32_t a_r2 = opaque(sb + SM_RED2 + g * 32 + warp * 4);
            const uint32_t a_f2 = opaque(sb + SM_RED2 + (lane & 7) * 32);
            const uint32_t a_ho = opaque(sb + SM_H + ((dn_idx >= 0 ? dn_idx * 8 : 0) + (lane & 7)) * 4);
            const uint32_t tag4 = tag & 15u;
            if (gu || warp == dn_idx / 10) {
                float xr[4];
#pragma unroll
                for (int e = 0; e < 4; e++) xr[e] = __bfloat162float(p.x[80 * warp + ucol(U, e)]);
                uint32_t n = 0;
                if (gu) {
                    mbar_wait(bar_w, 0);
#pragma unroll
                    for (int s = 0; s < 5; s++) {
                        const int row = 80 * warp + ucol(4 * s + (r >> 1), 2 * (mi >> 1) + (r & 1));
                        ldsm4t(wgf[s], sb + SM_WG + row * 32 + (mi & 1) * 16);
                        ldsm4t(wuf[s], sb + SM_WU + row * 32 + (mi & 1) * 16);
                    }
                }
                while (!__all_sync(0xffffffffu, ld_relaxed(bell_p) == tag)) {
                    if (++n > SPIN_LIMIT) __trap();
                }
                float s0, s1_, a2, a3;
#define SUM_Q(u) \
    s0 = (__uint_as_float(u[0].x) + __uint_as_float(u[1].x)) + (__uint_as_float(u[2].x) + __uint_as_float(u[3].x)); \
    s1_ = (__uint_as_float(u[0].y) + __uint_as_float(u[1].y)) + (__uint_as_float(u[2].y) + __uint_as_float(u[3].y)); \
    a2 = (__uint_as_float(u[0].z) + __uint_as_float(u[1].z)) + (__uint_as_float(u[2].z) + __uint_as_float(u[3].z)); \
    a3 = (__uint_as_float(u[0].w ^ tag4) + __uint_as_float(u[1].w ^ tag4)) + (__uint_as_float(u[2].w ^ tag4) + __uint_as_float(u[3].w ^ tag4));
                while (true) {
                    uint4 u[4];
#pragma unroll
                    for (int q = 0; q < 4; q++) u[q] = ll_load(attn_p + q * 256);
                    const uint32_t bad = (u[0].w ^ tag4) | (u[1].w ^ tag4) | (u[2].w ^ tag4) | (u[3].w ^ tag4);
                    SUM_Q(u)
                    if (__all_sync(0xffffffffu, (bad & 15u) == 0)) break;
                    if (++n > SPIN_LIMIT) __trap();
                }
#undef SUM_Q
                const uint32_t hb0 = pack_bf2(xr[0] + bfr(s0), xr[1] + bfr(s1_));
                const uint32_t hb1 = pack_bf2(xr[2] + bfr(a2), xr[3] + bfr(a3));
                const float h0 = bf_lo(hb0), h1 = bf_hi(hb0), h2 = bf_lo(hb1), h3 = bf_hi(hb1);
                if (lane < 20) {
                    sts32(a_h, h0);
                    sts32(a_h + 32, h1);
                    sts32(a_h2, h2);
                    sts32(a_h2 + 32, h3);
                }
                if (gu) {
                    uint32_t f0[5], f1[5];
                    const uint32_t t0 = lane < 20 ? hb0 : 0x3f803f80u, t1 = lane < 20 ? hb1 : 0x3f803f80u;
                    const float piv = __shfl_sync(0xffffffffu, h0, 0);
#pragma unroll
                    for (int s = 0; s < 5; s++) {
                        f0[s] = __shfl_sync(0xffffffffu, t0, g < 4 ? 4 * s + j : 31);
                        f1[s] = __shfl_sync(0xffffffffu, t1, g < 4 ? 4 * s + j : 31);
                    }
                    const float d0 = h0 - piv, d1 = h1 - piv, d2 = h2 - piv, d3 = h3 - piv;
                    float s1 = lane < 20 ? (d0 + d1) + (d2 + d3) : 0.f;
                    float s2 = lane < 20 ? fmaf(d0, d0, d1 * d1) + fmaf(d2, d2, d3 * d3) : 0.f;
                    float cg[2][4], cu[2][4];
#pragma unroll
                    for (int i = 0; i < 2; i++) {
                        cg[i][0] = cg[i][1] = cg[i][2] = cg[i][3] = 0.f;
                        cu[i][0] = cu[i][1] = cu[i][2] = cu[i][3] = 0.f;
                    }
#pragma unroll
                    for (int s = 0; s < 5; s++) {
                        const float t1 = __shfl_xor_sync(0xffffffffu, s1, 16 >> s);
                        const float t2 = __shfl_xor_sync(0xffffffffu, s2, 16 >> s);
                        mma16816(cg[s & 1], wgf[s][0], wgf[s][1], wgf[s][2], wgf[s][3], f0[s], f1[s]);
                        mma16816(cu[s & 1], wuf[s][0], wuf[s][1], wuf[s][2], wuf[s][3], f0[s], f1[s]);
                        s1 += t1;
                        s2 += t2;
                    }
                    const bool o1 = j & 1;
                    const float ga = o1 ? cg[0][2] + cg[1][2] : cg[0][0] + cg[1][0];
                    const float ua = o1 ? cu[0][2] + cu[1][2] : cu[0][0] + cu[1][0];
                    sts64(a_red, ga, ua);
                    if (lane == 0) sts128(a_st, fmaf(80.f, piv, s1), piv, 2.f * s1, s2);
                }
            }
            bar_sync(2, 256);
            if (gu && warp == 4) {
                float4 st[8], ra[8], rc[8];
#pragma unroll
                for (int w8 = 0; w8 < 8; w8++) st[w8] = lds128(sb + SM_ST + w8 * 16);
#pragma unroll
                for (int w8 = 0; w8 < 8; w8++) {
                    ra[w8] = lds128(a_fin + w8 * 256);
                    rc[w8] = lds128(a_fin + w8 * 256 + 128);
                }
#define SUM8(arr, f) (((arr[0].f + arr[1].f) + (arr[2].f + arr[3].f)) + ((arr[4].f + arr[5].f) + (arr[6].f + arr[7].f)))
                const float mean = SUM8(st, x) * (1.0f / DM);
#pragma unroll
                for (int w8 = 0; w8 < 8; w8++) {
                    const float dl = st[w8].y - mean;
                    st[w8].w = fmaf(dl, fmaf(80.f, dl, st[w8].z), st[w8].w);
                }
                const float var = fmaxf(SUM8(st, w) * (1.0f / DM), 0.f);
                const float rs = rcp_fast(bfr(sqrt_fast(bfr(bfr(var) + 1e-5f))));
                const float mean_b = bfr(mean);
                const float g0 = bfr(fmaf(-mean_b, SUM8(rc, x), SUM8(ra, x)) * rs), u0 = bfr(fmaf(-mean_b, SUM8(rc, y), SUM8(ra, y)) * rs);
                const float g1 = bfr(fmaf(-mean_b, SUM8(rc, z), SUM8(ra, z)) * rs), u1 = bfr(fmaf(-mean_b, SUM8(rc, w), SUM8(ra, w)) * rs);
#undef SUM8
                const float act0 = bfr(g0 * rcp_fast(1.0f + ex2(-LOG2E * g0))) * u0;
                const float act1 = bfr(g1 * rcp_fast(1.0f + ex2(-LOG2E * g1))) * u1;
                const uint32_t pk = pack_bf2(act0, act1);
                const uint32_t pn = __shfl_down_sync(0xffffffffu, pk, 1);
                if (lane < 8 && !(lane & 1)) ll_store(act_st, pk, pn, 0u, tag);
            }
            if (dn_idx >= 0) {
                const float hres = lds32(a_ho);
                mbar_wait(bar_w + 8, 0);
                {
                    const uint32_t wa = sb + SM_WD + (192 * warp + 16 * (mi & 1) + 4 * (r >> 1) + 2 * (mi >> 1) + (r & 1)) * 16;
#pragma unroll
                    for (int s = 0; s < 6; s++) ldsm4t(wdf[s], wa + s * 512);
                }
                uint2 u0, u1;
                uint32_t n = 0;
                while (true) {
                    const uint4 a0 = ll_load(act_p0), a1 = ll_load(act_p1);
                    u0 = make_uint2(a0.x, a0.y);
                    u1 = make_uint2(a1.x, a1.y);
                    if (__all_sync(0xffffffffu, a0.w == tag && a1.w == tag)) break;
                    if (++n > SPIN_LIMIT) __trap();
                }
                float c[3][4];
#pragma unroll
                for (int i = 0; i < 3; i++) c[i][0] = c[i][1] = c[i][2] = c[i][3] = 0.f;
#pragma unroll
                for (int i = 0; i < 6; i++) {
                    const bool on = (g >> 1) == (i < 4 ? i : i - 4);
                    const uint32_t e0 = on ? (i < 4 ? u0.x : u1.x) : 0u, e1 = on ? (i < 4 ? u0.y : u1.y) : 0u;
                    mma16816(c[i % 3], wdf[i][0], wdf[i][1], wdf[i][2], wdf[i][3], e0, e1);
                }
                float e0 = ((c[0][0] + c[0][3]) + (c[1][0] + c[1][3])) + (c[2][0] + c[2][3]);
                e0 += __shfl_xor_sync(0xffffffffu, e0, 1);
                e0 += __shfl_xor_sync(0xffffffffu, e0, 2);
                if (j == 0) sts32(a_r2, e0);
                bar_sync(2, 256);
                if (warp == 4 && lane < 8) {
                    const float4 ra = lds128(a_f2), rb = lds128(a_f2 + 16);
                    const float sum = ((ra.x + ra.y) + (ra.z + ra.w)) + ((rb.x + rb.y) + (rb.z + rb.w));
                    const uint32_t res = pack_bf2(hres + bfr(sum), 0.f);
                    asm volatile("st.global.u16 [%0], %1;" ::"l"(out_p), "h"((unsigned short)res) : "memory");
                    if (lane == 0 && cta == NS - 1) *(volatile unsigned int*)&g_epoch = tag;
                }
            }
        }
    } else {
        const int qd = cta - NS;
        if (warp == 8) {
            if (lane == 0) {
                for (int s = 0; s < NWO; s++) {
                    mbar_init(bar_full + 8 * s, 1);
                    mbar_init(bar_empty + 8 * s, 8);
                }
                asm volatile("fence.mbarrier_init.release.cluster;" ::: "memory");
            }
            __syncwarp();
            asm volatile("bar.arrive 1, 288;" ::: "memory");
            uint64_t pol;
            asm volatile("createpolicy.fractional.L2::evict_first.b64 %0, 1.0;" : "=l"(pol));
            int slot = 0;
            uint32_t ph = 0;
            for (int h = 0; h < NH; h++) {
                if (lane == 0) {
                    if (h >= NWO) mbar_wait(bar_empty + 8 * slot, ph ^ 1);
                    mbar_expect_tx(bar_full + 8 * slot, 48 * DM * 2);
                }
                __syncwarp();
                const __nv_bfloat16* src = p.wo + (size_t)(h * DH + qd * 48) * DM;
                bulk_load(sb + slot * WO_BUF + lane * WO_PITCH, src + lane * DM, DM * 2, bar_full + 8 * slot, pol);
                if (lane < 16)
                    bulk_load(sb + slot * WO_BUF + (32 + lane) * WO_PITCH, src + (32 + lane) * DM, DM * 2,
                              bar_full + 8 * slot, pol);
                if (++slot == NWO) { slot = 0; ph ^= 1; }
            }
            return;
        }
        if (warp == 9) return;
        if (tid == 255) *tag_s = *(volatile unsigned int*)&g_epoch + 1;
        bar_sync(1, 288);
        const uint32_t tag = *tag_s;
        float acc[5][4];
#pragma unroll
        for (int t = 0; t < 5; t++) acc[t][0] = acc[t][1] = acc[t][2] = acc[t][3] = 0.f;
        const uint32_t a_ow = opaque(sb + SC_OB + warp * 192 + (lane & 15) * 12);
        const uint32_t a_or = opaque(sb + SC_OB + (lane < 24 ? lane : 0) * 8);
        uint4* attn_st = opaque(&g_attn[qd][warp][j == 0 ? g : j == 1 ? 8 + g : 16 + (g >> 1)]);
        const int mi = lane >> 3, r = lane & 7;
        const uint32_t woff = sb + (r + 8 * (mi >> 1)) * WO_PITCH + (80 * warp + 8 * (mi & 1)) * 2;
        const int dc = 2 * warp + (lane >> 4);
        int slot = 0;
        uint32_t ph = 0;
        const uint4* hp0 = &g_phdr[0][lane];
        const uint4* dp0 = &g_pdat[0][qd][dc][lane & 15];
        unsigned int* bell_st = opaque(&g_bell[lane][qd]);
        if (warp == 0) st_relaxed(bell_st, 0u);
        for (int h = 0; h < NH; h++) {
            const uint4* hp = opaque(hp0 + h * MAXS);
            const uint4* dp = opaque(dp0 + h * (NCOMB * MAXS * 16));
            uint32_t wf[5][3][4];
            mbar_wait(bar_full + 8 * slot, ph);
#pragma unroll
            for (int t = 0; t < 5; t++)
#pragma unroll
                for (int s = 0; s < 3; s++) ldsm4t(wf[t][s], woff + slot * WO_BUF + s * 16 * WO_PITCH + t * 32);
            __syncwarp();
            if (lane == 0) mbar_arrive(bar_empty + 8 * slot);
            if (++slot == NWO) { slot = 0; ph ^= 1; }

            uint4 hd[4], u[8];
#pragma unroll
            for (int i = 0; i < 4; i++) hd[i] = make_uint4(__float_as_uint(NEG_INF), 0u, 0u, lane + 32 * i < NS ? ~tag : tag);
#pragma unroll
            for (int i = 0; i < 8; i++) u[i] = make_uint4(0u, 0u, 0u, dc + 16 * i < NS ? ~tag : tag);
            uint32_t n = 0;
            if (h < NH - 1) {
                while (true) {
                    bool ok = true;
#pragma unroll
                    for (int i = 0; i < 4; i++)
                        if (hd[i].w != tag) hd[i] = ll_load(hp + 32 * i);
#pragma unroll
                    for (int i = 0; i < 4; i++) ok = ok && (hd[i].w == tag);
                    if (__all_sync(0xffffffffu, ok)) break;
                    if (++n > SPIN_LIMIT) __trap();
                    __nanosleep(1000);
                }
            }
            while (true) {
                bool ok = true;
#pragma unroll
                for (int i = 0; i < 4; i++)
                    if (hd[i].w != tag) hd[i] = ll_load(hp + 32 * i);
#pragma unroll
                for (int i = 0; i < 8; i++)
                    if (u[i].w != tag) u[i] = ll_load(dp + 256 * i);
#pragma unroll
                for (int i = 0; i < 4; i++) ok = ok && (hd[i].w == tag);
#pragma unroll
                for (int i = 0; i < 8; i++) ok = ok && (u[i].w == tag);
                if (__all_sync(0xffffffffu, ok)) break;
                if (++n > SPIN_LIMIT) __trap();
            }
            if (h == NH - 1 && warp == 0) st_relaxed(bell_st, tag);
            const float M = warp_max(fmaxf(fmaxf(__uint_as_float(hd[0].x), __uint_as_float(hd[1].x)),
                                           fmaxf(__uint_as_float(hd[2].x), __uint_as_float(hd[3].x))));
            float f[4];
#pragma unroll
            for (int i = 0; i < 4; i++) f[i] = ex2(__uint_as_float(hd[i].x) - M);
            float L = fmaf(f[0], __uint_as_float(hd[0].y), f[1] * __uint_as_float(hd[1].y)) +
                      fmaf(f[2], __uint_as_float(hd[2].y), f[3] * __uint_as_float(hd[3].y));
            float fa[4], fb[4];
#pragma unroll
            for (int i = 0; i < 4; i++) {
                fa[i] = __shfl_sync(0xffffffffu, f[i], dc);
                fb[i] = __shfl_sync(0xffffffffu, f[i], dc + 16);
            }
            L += __shfl_xor_sync(0xffffffffu, L, 16);
            float o0 = 0.f, o1 = 0.f, o2 = 0.f, o3 = 0.f, o4 = 0.f, o5 = 0.f;
#pragma unroll
            for (int i = 0; i < 4; i++) {
                o0 = fmaf(fa[i], __uint_as_float(u[2 * i].x), o0);
                o1 = fmaf(fa[i], __uint_as_float(u[2 * i].y), o1);
                o2 = fmaf(fa[i], __uint_as_float(u[2 * i].z), o2);
                o3 = fmaf(fb[i], __uint_as_float(u[2 * i + 1].x), o3);
                o4 = fmaf(fb[i], __uint_as_float(u[2 * i + 1].y), o4);
                o5 = fmaf(fb[i], __uint_as_float(u[2 * i + 1].z), o5);
            }
            L += __shfl_xor_sync(0xffffffffu, L, 8);
            o0 += o3;
            o1 += o4;
            o2 += o5;
            o0 += __shfl_xor_sync(0xffffffffu, o0, 16);
            o1 += __shfl_xor_sync(0xffffffffu, o1, 16);
            o2 += __shfl_xor_sync(0xffffffffu, o2, 16);
            L += __shfl_xor_sync(0xffffffffu, L, 4);
            const uint32_t par = (h & 1) * (8 * 192);
            if (lane < 16) {
                sts32(a_ow + par, o0);
                sts32(a_ow + par + 4, o1);
                sts32(a_ow + par + 8, o2);
            }
            bar_sync(2, 256);
            L += __shfl_xor_sync(0xffffffffu, L, 2);
            L += __shfl_xor_sync(0xffffffffu, L, 1);
            const float rL = rcp_fast(L);
            float2 ov[8];
#pragma unroll
            for (int w8 = 0; w8 < 8; w8++) ov[w8] = lds64(a_or + par + w8 * 192);
            const float e0 = ((ov[0].x + ov[1].x) + (ov[2].x + ov[3].x)) + ((ov[4].x + ov[5].x) + (ov[6].x + ov[7].x));
            const float e1 = ((ov[0].y + ov[1].y) + (ov[2].y + ov[3].y)) + ((ov[4].y + ov[5].y) + (ov[6].y + ov[7].y));
            const uint32_t pk = pack_bf2(e0 * rL, e1 * rL);
            uint32_t b0[3], b1[3];
#pragma unroll
            for (int s = 0; s < 3; s++) {
                b0[s] = __shfl_sync(0xffffffffu, pk, 8 * s + j);
                b1[s] = __shfl_sync(0xffffffffu, pk, 8 * s + 4 + j);
            }
#pragma unroll
            for (int s = 0; s < 3; s++)
#pragma unroll
                for (int t = 4; t >= 0; t--)
                    mma16816(acc[t], wf[t][s][0], wf[t][s][1], wf[t][s][2], wf[t][s][3], b0[s], b1[s]);
            const float n8 = __shfl_down_sync(0xffffffffu, acc[4][0], 4), n9 = __shfl_down_sync(0xffffffffu, acc[4][2], 4);
            const float v0 = j == 0 ? acc[0][0] : j == 1 ? acc[2][0] : acc[4][0];
            const float v1 = j == 0 ? acc[0][2] : j == 1 ? acc[2][2] : acc[4][2];
            const float v2 = j == 0 ? acc[1][0] : j == 1 ? acc[3][0] : n8;
            const float v3 = j == 0 ? acc[1][2] : j == 1 ? acc[3][2] : n9;
            if (j < 2 || (j == 2 && !(g & 1)))
                ll_store(attn_st, __float_as_uint(v0), __float_as_uint(v1), __float_as_uint(v2),
                         (__float_as_uint(v3) & ~15u) | ((tag & 15u) ^ (h == NH - 1 ? 0u : 8u)));
        }
    }
}

}

extern "C" void kernel_launch(void* const* d_in, const int* in_sizes, int n_in, void* d_out, int out_size) {
    using namespace fused;
    static int grid = 0;
    static CUtensorMap tm[4];
    static const void* tm_ptr[4] = {nullptr, nullptr, nullptr, nullptr};
    if (grid == 0) {
        int dev = 0, sms = 0;
        cudaGetDevice(&dev);
        cudaDeviceGetAttribute(&sms, cudaDevAttrMultiProcessorCount, dev);
        cudaFuncSetAttribute(fused_kernel, cudaFuncAttributeMaxDynamicSharedMemorySize, SM_TOTAL);
        grid = sms < MAXS + NCOMB ? sms : MAXS + NCOMB;
    }
    {
        const int idx[4] = {3, 6, 7, 8};
        const cuuint64_t cols[4] = {HD, FF, FF, DM}, rows[4] = {DM, DM, DM, FF};
        const cuuint32_t bc[4] = {48, 16, 16, 8}, br[4] = {WQ_BOX_ROWS, 160, 160, 256};
        for (int i = 0; i < 4; i++) {
            if (tm_ptr[i] == d_in[idx[i]]) continue;
            typedef CUresult (*EncodeFn)(CUtensorMap*, CUtensorMapDataType, cuuint32_t, void*, const cuuint64_t*,
                                         const cuuint64_t*, const cuuint32_t*, const cuuint32_t*, CUtensorMapInterleave,
                                         CUtensorMapSwizzle, CUtensorMapL2promotion, CUtensorMapFloatOOBfill);
            void* fn = nullptr;
            cudaDriverEntryPointQueryResult qr;
            cudaGetDriverEntryPoint("cuTensorMapEncodeTiled", &fn, cudaEnableDefault, &qr);
            cuuint64_t gdim[2] = {cols[i], rows[i]};
            cuuint64_t gstr[1] = {cols[i] * 2};
            cuuint32_t box[2] = {bc[i], br[i]};
            cuuint32_t estr[2] = {1, 1};
            ((EncodeFn)fn)(&tm[i], CU_TENSOR_MAP_DATA_TYPE_BFLOAT16, 2, d_in[idx[i]], gdim, gstr, box, estr,
                           CU_TENSOR_MAP_INTERLEAVE_NONE, CU_TENSOR_MAP_SWIZZLE_NONE,
                           CU_TENSOR_MAP_L2_PROMOTION_L2_128B, CU_TENSOR_MAP_FLOAT_OOB_FILL_NONE);
            tm_ptr[i] = d_in[idx[i]];
        }
    }
    Params p;
    p.x = (const __nv_bfloat16*)d_in[0];
    p.k = (const char*)d_in[1];
    p.v = (const char*)d_in[2];
    p.wo = (const __nv_bfloat16*)d_in[4];
    p.out = (__nv_bfloat16*)d_out;
    fused_kernel<<<grid, NTHREADS, SM_TOTAL, cudaStreamPerThread>>>(p, tm[0], tm[1], tm[2], tm[3]);
}
```

```cpp
#include <cuda_runtime.h>
#include <cuda.h>
#include <cuda_bf16.h>
#include <stdint.h>

namespace fused {

constexpr int DM = 640;
constexpr int NH = 32;
constexpr int SK = 32768;
constexpr int DH = 192;
constexpr int HD = NH * DH;
constexpr int FF = 1536;
constexpr int ROWB = DH * 2;
constexpr int ITEM_KEYS = 64;
constexpr int CHUNK = ITEM_KEYS * ROWB;
constexpr int ITEMS_PER_HEAD = SK / ITEM_KEYS;
constexpr int NITEMS = NH * ITEMS_PER_HEAD;
constexpr int NSLOT = 6;
constexpr int NPRE = NSLOT / 2;
constexpr int NCOMB = 4;
constexpr int COMB_AT = 40;
constexpr int MAXS = 128;
constexpr int NGU = FF / 16;
constexpr int NDN = DM / 8;
constexpr int DELAY_GU = 1000;
constexpr int DELAY_D = 3000;
constexpr int NQS = HD / 48;
constexpr int WQ_BOX_ROWS = 160;
constexpr int NTHREADS = 320;

constexpr int SM_RING = 0;
constexpr int SM_WG = NSLOT * CHUNK;
constexpr int SM_WU = SM_WG + DM * 32;
constexpr int SM_WD = SM_WU + DM * 32;
constexpr int SM_Q = SM_WD + FF * 16;
constexpr int SM_OBUF = SM_Q + HD * 2;
constexpr int SM_ML = SM_OBUF + 2 * 4 * DH * 4;
constexpr int SM_BAR = SM_ML + 160;
constexpr int SM_META = SM_BAR + 20 * 8;
constexpr int SM_TAG = SM_META + 16;
constexpr int SM_TOTAL = SM_TAG + 16;
constexpr int SM_XS = SM_Q;
constexpr int SM_XN = SM_Q + DM * 4;
constexpr int SM_QRED = SM_XN + DM * 2;
constexpr int SM_WQ = SM_WG;
constexpr int SM_H = 0;
constexpr int SM_RED = DM * 4;
constexpr int SM_RED2 = SM_RED + 8 * 64 * 4;
constexpr int SM_ST = SM_RED2 + 8 * 8 * 4;
constexpr int WO_PITCH = DM * 2 + 16;
constexpr int WO_BUF = 48 * WO_PITCH;
constexpr int NWO = 3;
constexpr int SC_OB = NWO * WO_BUF;
static_assert(SC_OB + 2 * 8 * 48 * 4 <= SM_BAR, "combine smem overlaps barriers");
static_assert(SM_TOTAL <= 232448, "smem");

constexpr float LOG2E = 1.4426950408889634f;
constexpr float QK_SCALE = 0.07216878364870322f;
constexpr float NEG_INF = -__builtin_huge_valf();

__device__ unsigned int g_epoch;
__device__ unsigned int g_work;
__device__ unsigned int g_exit;
__device__ uint4 g_q[HD / 6];
__device__ uint4 g_phdr[NH][MAXS];
__device__ uint4 g_pdat[NH][NCOMB][MAXS][16];
__device__ uint4 g_attn[NCOMB][8][32];
__device__ uint4 g_act[NGU][4];
__device__ unsigned int g_bell[32][32];

__device__ __forceinline__ uint32_t s2u(const void* p) { return (uint32_t)__cvta_generic_to_shared(p); }
__device__ __forceinline__ uint32_t pack_bf2(float lo, float hi) {
    uint32_t r;
    asm("cvt.rn.bf16x2.f32 %0, %1, %2;" : "=r"(r) : "f"(hi), "f"(lo));
    return r;
}
__device__ __forceinline__ float bfr(float x) { return __uint_as_float(pack_bf2(0.f, x)); }
template <typename T>
__device__ __forceinline__ T* opaque(T* p) {
    asm volatile("" : "+l"(p));
    return p;
}
__device__ __forceinline__ uint32_t opaque(uint32_t v) {
    asm volatile("" : "+r"(v));
    return v;
}
__device__ __forceinline__ float4 lds128(uint32_t a) {
    float4 v;
    asm volatile("ld.shared.v4.f32 {%0,%1,%2,%3}, [%4];" : "=f"(v.x), "=f"(v.y), "=f"(v.z), "=f"(v.w) : "r"(a) : "memory");
    return v;
}
__device__ __forceinline__ float2 lds64(uint32_t a) {
    float2 v;
    asm volatile("ld.shared.v2.f32 {%0,%1}, [%2];" : "=f"(v.x), "=f"(v.y) : "r"(a) : "memory");
    return v;
}
__device__ __forceinline__ float lds32(uint32_t a) {
    float v;
    asm volatile("ld.shared.f32 %0, [%1];" : "=f"(v) : "r"(a) : "memory");
    return v;
}
__device__ __forceinline__ void sts128(uint32_t a, float x, float y, float z, float w) {
    asm volatile("st.shared.v4.f32 [%0], {%1,%2,%3,%4};" ::"r"(a), "f"(x), "f"(y), "f"(z), "f"(w) : "memory");
}
__device__ __forceinline__ void sts64(uint32_t a, float x, float y) {
    asm volatile("st.shared.v2.f32 [%0], {%1,%2};" ::"r"(a), "f"(x), "f"(y) : "memory");
}
__device__ __forceinline__ void sts32(uint32_t a, float x) {
    asm volatile("st.shared.f32 [%0], %1;" ::"r"(a), "f"(x) : "memory");
}
__device__ __forceinline__ float bf_lo(uint32_t v) { return __uint_as_float(v << 16); }
__device__ __forceinline__ float bf_hi(uint32_t v) { return __uint_as_float(v & 0xffff0000u); }
__device__ __forceinline__ float ex2(float x) {
    float r;
    asm("ex2.approx.ftz.f32 %0, %1;" : "=f"(r) : "f"(x));
    return r;
}
__device__ __forceinline__ float rcp_fast(float x) {
    float r;
    asm("rcp.approx.ftz.f32 %0, %1;" : "=f"(r) : "f"(x));
    return r;
}
__device__ __forceinline__ float sqrt_fast(float x) {
    float r;
    asm("sqrt.approx.ftz.f32 %0, %1;" : "=f"(r) : "f"(x));
    return r;
}
__device__ __forceinline__ uint32_t ld_relaxed(const unsigned int* p) {
    uint32_t v;
    asm volatile("ld.relaxed.gpu.global.u32 %0, [%1];" : "=r"(v) : "l"(p) : "memory");
    return v;
}
__device__ __forceinline__ void st_relaxed(unsigned int* p, uint32_t v) {
    asm volatile("st.relaxed.gpu.global.u32 [%0], %1;" ::"l"(p), "r"(v) : "memory");
}
__device__ __forceinline__ void mbar_init(uint32_t bar, uint32_t cnt) {
    asm volatile("mbarrier.init.shared.b64 [%0], %1;" ::"r"(bar), "r"(cnt) : "memory");
}
__device__ __forceinline__ void mbar_expect_tx(uint32_t bar, uint32_t bytes) {
    asm volatile("mbarrier.arrive.expect_tx.shared.b64 _, [%0], %1;" ::"r"(bar), "r"(bytes) : "memory");
}
__device__ __forceinline__ void mbar_arrive(uint32_t bar) {
    asm volatile("mbarrier.arrive.shared.b64 _, [%0];" ::"r"(bar) : "memory");
}
__device__ __forceinline__ bool mbar_try(uint32_t bar, uint32_t parity) {
    uint32_t ok;
    asm volatile(
        "{\n .reg .pred p;\n mbarrier.try_wait.parity.shared.b64 p, [%1], %2;\n selp.u32 %0, 1, 0, p;\n}"
        : "=r"(ok)
        : "r"(bar), "r"(parity)
        : "memory");
    return ok != 0;
}
constexpr uint32_t SPIN_LIMIT = 1u << 24;
__device__ __forceinline__ void mbar_wait(uint32_t bar, uint32_t parity) {
    uint32_t n = 0;
    while (!mbar_try(bar, parity)) {
        if (++n > SPIN_LIMIT) __trap();
    }
}
__device__ __forceinline__ void bulk_load(uint32_t dst, const void* src, uint32_t bytes, uint32_t bar, uint64_t pol) {
    asm volatile(
        "cp.async.bulk.shared::cluster.global.mbarrier::complete_tx::bytes.L2::cache_hint [%0], [%1], %2, [%3], %4;"
        ::"r"(dst), "l"(src), "r"(bytes), "r"(bar), "l"(pol)
        : "memory");
}
__device__ __forceinline__ void tma_load_2d(uint32_t dst, const CUtensorMap* tm, int c0, int c1, uint32_t bar) {
    asm volatile(
        "cp.async.bulk.tensor.2d.shared::cluster.global.mbarrier::complete_tx::bytes [%0], [%1, {%3, %4}], [%2];"
        ::"r"(dst), "l"(tm), "r"(bar), "r"(c0), "r"(c1)
        : "memory");
}
__device__ __forceinline__ void ll_store(uint4* p, uint32_t a, uint32_t b, uint32_t c, uint32_t tag) {
    asm volatile(
        "{\n .reg .b128 t;\n .reg .b64 lo, hi;\n mov.b64 lo, {%1, %2};\n mov.b64 hi, {%3, %4};\n"
        " mov.b128 t, {lo, hi};\n st.relaxed.gpu.global.b128 [%0], t;\n}"
        ::"l"(p), "r"(a), "r"(b), "r"(c), "r"(tag)
        : "memory");
}
__device__ __forceinline__ uint4 ll_load(const uint4* p) {
    uint4 v;
    asm volatile(
        "{\n .reg .b128 t;\n .reg .b64 lo, hi;\n ld.relaxed.gpu.global.b128 t, [%4];\n"
        " mov.b128 {lo, hi}, t;\n mov.b64 {%0, %1}, lo;\n mov.b64 {%2, %3}, hi;\n}"
        : "=r"(v.x), "=r"(v.y), "=r"(v.z), "=r"(v.w)
        : "l"(p)
        : "memory");
    return v;
}
__device__ __forceinline__ void ldsm4(uint32_t (&r)[4], uint32_t addr) {
    asm volatile("ldmatrix.sync.aligned.m8n8.x4.shared.b16 {%0,%1,%2,%3}, [%4];"
                 : "=r"(r[0]), "=r"(r[1]), "=r"(r[2]), "=r"(r[3])
                 : "r"(addr)
                 : "memory");
}
__device__ __forceinline__ void ldsm4t(uint32_t (&r)[4], uint32_t addr) {
    asm volatile("ldmatrix.sync.aligned.m8n8.x4.trans.shared.b16 {%0,%1,%2,%3}, [%4];"
                 : "=r"(r[0]), "=r"(r[1]), "=r"(r[2]), "=r"(r[3])
                 : "r"(addr)
                 : "memory");
}
__device__ __forceinline__ void mma16816(float (&c)[4], uint32_t a0, uint32_t a1, uint32_t a2, uint32_t a3,
                                         uint32_t b0, uint32_t b1) {
    asm volatile(
        "mma.sync.aligned.m16n8k16.row.col.f32.bf16.bf16.f32 {%0,%1,%2,%3}, {%4,%5,%6,%7}, {%8,%9}, {%0,%1,%2,%3};"
        : "+f"(c[0]), "+f"(c[1]), "+f"(c[2]), "+f"(c[3])
        : "r"(a0), "r"(a1), "r"(a2), "r"(a3), "r"(b0), "r"(b1));
}
__device__ __forceinline__ void bar_sync(int id, int n) {
    __syncwarp();
    asm volatile("bar.sync %0, %1;" ::"r"(id), "r"(n) : "memory");
}
__device__ __forceinline__ void delay_cycles(uint32_t c) {
    uint32_t t0, t1;
    asm volatile("mov.u32 %0, %clock;" : "=r"(t0)::"memory");
    do {
        asm volatile("mov.u32 %0, %clock;" : "=r"(t1)::"memory");
    } while (t1 - t0 < c);
}
__device__ __forceinline__ float warp_max(float v) {
    int k = __float_as_int(v);
    k ^= (k >> 31) & 0x7fffffff;
    k = __reduce_max_sync(0xffffffffu, k);
    k ^= (k >> 31) & 0x7fffffff;
    return __int_as_float(k);
}

__device__ __forceinline__ void ln_stats(const float* v, int lane, float& mean_b, float& sd_b) {
    const float4* v4 = reinterpret_cast<const float4*>(v);
    float piv = v[0];
    float s1 = 0.f, s2 = 0.f;
#pragma unroll
    for (int i = 0; i < 5; i++) {
        float4 a = v4[lane + 32 * i];
        float d0 = a.x - piv, d1 = a.y - piv, d2 = a.z - piv, d3 = a.w - piv;
        s1 += (d0 + d1) + (d2 + d3);
        s2 += (d0 * d0 + d1 * d1) + (d2 * d2 + d3 * d3);
    }
#pragma unroll
    for (int o = 16; o > 0; o >>= 1) {
        s1 += __shfl_xor_sync(0xffffffffu, s1, o);
        s2 += __shfl_xor_sync(0xffffffffu, s2, o);
    }
    float md = s1 * (1.0f / DM);
    float var = fmaxf(s2 * (1.0f / DM) - md * md, 0.f);
    mean_b = bfr(piv + md);
    sd_b = bfr(__fsqrt_rn(bfr(bfr(var) + 1e-5f)));
}
__device__ __forceinline__ float ln_apply(float x, float mean_b, float sd_b) {
    return bfr(__fdiv_rn(bfr(x - mean_b), sd_b));
}

struct Params {
    const __nv_bfloat16* x;
    const char* k;
    const char* v;
    const __nv_bfloat16* wo;
    __nv_bfloat16* out;
};

__global__ void __launch_bounds__(NTHREADS, 1)
fused_kernel(const Params p, const __grid_constant__ CUtensorMap tm_wq, const __grid_constant__ CUtensorMap tm_wg,
             const __grid_constant__ CUtensorMap tm_wu, const __grid_constant__ CUtensorMap tm_wd) {
    extern __shared__ __align__(1024) unsigned char smem[];
    const uint32_t sb = opaque(s2u(smem));
    const int tid = threadIdx.x, warp = tid >> 5, lane = tid & 31;
    const int g = lane >> 2, j = lane & 3;
    const int NS = gridDim.x - NCOMB;
    const int bx = blockIdx.x;
    const int cta = bx < COMB_AT ? bx : bx < COMB_AT + NCOMB ? NS + bx - COMB_AT : bx - NCOMB;
    const uint32_t bar_full = sb + SM_BAR, bar_empty = sb + SM_BAR + 8 * NSLOT, bar_wq = sb + SM_BAR + 16 * NSLOT;
    const uint32_t bar_q = bar_wq + 16, bar_w = bar_q + 8;
    volatile int* meta = reinterpret_cast<volatile int*>(smem + SM_META);
    volatile uint32_t* tag_s = reinterpret_cast<volatile uint32_t*>(smem + SM_TAG);

    if (tid == 256 && cta < NS) {
        asm volatile("cp.async.bulk.prefetch.L2.global [%0], %1;" ::"l"(p.k + (size_t)cta * CHUNK), "r"(CHUNK / 4) : "memory");
        mbar_init(bar_wq, 1);
        mbar_init(bar_wq + 8, 1);
        asm volatile("fence.mbarrier_init.release.cluster;" ::: "memory");
#pragma unroll
        for (int i = 0; i < 4; i++) {
            if (!(i & 1)) mbar_expect_tx(bar_wq + 4 * i, DM * 48);
            tma_load_2d(sb + SM_WQ + i * WQ_BOX_ROWS * 96, &tm_wq, cta * 48, i * WQ_BOX_ROWS, bar_wq + 8 * (i >> 1));
        }
    }

    if (cta < NS) {
        if (warp == 8) {
            if (lane == 0) {
                for (int s = 0; s < NSLOT; s++) {
                    mbar_init(bar_full + 8 * s, 1);
                    mbar_init(bar_empty + 8 * s, 4);
                }
                mbar_init(bar_q, 4);
                for (int i = 0; i < 2; i++) mbar_init(bar_w + 8 * i, 1);
                meta[3] = 0;
                asm volatile("fence.mbarrier_init.release.cluster;" ::: "memory");
            }
            __syncwarp();
            asm volatile("bar.arrive 1, 320;" ::: "memory");
            if (lane == 0) {
                uint64_t pol;
                asm volatile("createpolicy.fractional.L2::evict_first.b64 %0, 1.0;" : "=l"(pol));
#pragma unroll
                for (int c = 0; c < NSLOT; c++) {
                    mbar_wait(c < 2 ? bar_wq + 8 * c : bar_full + 8 * (c - 2), 0);
                    const int item = cta + NS * (c >> 1);
                    if (!(c & 1)) meta[c >> 1] = item;
                    mbar_expect_tx(bar_full + 8 * c, CHUNK);
                    bulk_load(sb + SM_RING + c * CHUNK, ((c & 1) ? p.v : p.k) + (size_t)item * CHUNK, CHUNK,
                              bar_full + 8 * c, pol);
                }
                int slot = 0;
                uint32_t ph = 1;
                int lslot = NSLOT - 2;
                uint32_t lph = 0;
                while (true) {
                    mbar_wait(bar_full + 8 * lslot, lph);
                    mbar_wait(bar_empty + 8 * slot, ph ^ 1);
                    const int item = NS * NPRE + (int)atomicAdd(&g_work, 1u);
                    if (item >= NITEMS) break;
                    meta[slot >> 1] = item;
                    mbar_expect_tx(bar_full + 8 * slot, CHUNK);
                    bulk_load(sb + SM_RING + slot * CHUNK, p.k + (size_t)item * CHUNK, CHUNK, bar_full + 8 * slot, pol);
                    mbar_wait(bar_empty + 8 * slot + 8, ph ^ 1);
                    mbar_expect_tx(bar_full + 8 * slot + 8, CHUNK);
                    bulk_load(sb + SM_RING + (slot + 1) * CHUNK, p.v + (size_t)item * CHUNK, CHUNK, bar_full + 8 * slot + 8, pol);
                    lslot = slot;
                    lph = ph;
                    slot += 2;
                    if (slot == NSLOT) { slot = 0; ph ^= 1; }
                }
                meta[slot >> 1] = -1;
                meta[3] = 1;
                mbar_arrive(bar_full + 8 * slot);
                unsigned int e = atomicAdd(&g_exit, 1u);
                if (e == (unsigned)NS - 1) {
                    *(volatile unsigned int*)&g_work = 0;
                    *(volatile unsigned int*)&g_exit = 0;
                }
            }
            return;
        }
        float* xs = reinterpret_cast<float*>(smem + SM_XS);
        const int dn_idx = cta - (NS - NDN);
        if (warp == 9) {
            uint2 xv[5];
#pragma unroll
            for (int i = 0; i < 5; i++) xv[i] = *reinterpret_cast<const uint2*>(p.x + 4 * (lane + 32 * i));
            if (lane == 0) *tag_s = *(volatile unsigned int*)&g_epoch + 1;
#pragma unroll
            for (int i = 0; i < 5; i++)
                *reinterpret_cast<float4*>(xs + 4 * (lane + 32 * i)) =
                    make_float4(bf_lo(xv[i].x), bf_hi(xv[i].x), bf_lo(xv[i].y), bf_hi(xv[i].y));
            __syncwarp();
            float mean_b, sd_b;
            ln_stats(xs, lane, mean_b, sd_b);
#pragma unroll
            for (int i = 0; i < 5; i++)
                *reinterpret_cast<uint2*>(smem + SM_XN + 8 * (lane + 32 * i)) =
                    make_uint2(pack_bf2(ln_apply(bf_lo(xv[i].x), mean_b, sd_b), ln_apply(bf_hi(xv[i].x), mean_b, sd_b)),
                               pack_bf2(ln_apply(bf_lo(xv[i].y), mean_b, sd_b), ln_apply(bf_hi(xv[i].y), mean_b, sd_b)));
            bar_sync(1, 320);
            if (lane == 0) {
                mbar_wait(bar_q, 0);
                asm volatile("fence.proxy.async.shared::cta;" ::: "memory");
                bool warm = false;
                for (uint32_t n = 0; meta[3] == 0; n++) {
                    const int left = NITEMS - NS * NPRE - (int)ld_relaxed(&g_work);
                    if (left <= 0) break;
                    if (left < 512 && !warm) {
                        asm volatile("prefetch.tensormap [%0];" ::"l"(&tm_wg) : "memory");
                        asm volatile("prefetch.tensormap [%0];" ::"l"(&tm_wu) : "memory");
                        asm volatile("prefetch.tensormap [%0];" ::"l"(&tm_wd) : "memory");
                        warm = true;
                    }
                    for (int i = left / 256; i > 0 && meta[3] == 0; i--) __nanosleep(1000);
                    __nanosleep(100);
                    if (n > SPIN_LIMIT) __trap();
                }
                delay_cycles(DELAY_GU);
                if (cta < NGU) {
                    mbar_expect_tx(bar_w, DM * 64);
                    for (int i = 0; i < 4; i++) {
                        tma_load_2d(sb + SM_WG + i * 5120, &tm_wg, cta * 16, i * 160, bar_w);
                        tma_load_2d(sb + SM_WU + i * 5120, &tm_wu, cta * 16, i * 160, bar_w);
                    }
                }
                if (dn_idx >= 0) {
                    delay_cycles(DELAY_D);
                    mbar_expect_tx(bar_w + 8, FF * 16);
                    for (int i = 0; i < 6; i++) tma_load_2d(sb + SM_WD + i * 4096, &tm_wd, dn_idx * 8, i * 256, bar_w + 8);
                }
            }
            return;
        }
        float* qred = reinterpret_cast<float*>(smem + SM_QRED);
        if (tid < 8)
            for (int slice = cta; slice < NQS; slice += NS) ll_store(&g_q[slice * 8 + tid], 0u, 0u, 0u, 0u);
        if (warp == 4 && lane < 8 && !(lane & 1) && cta < NGU) ll_store(&g_act[cta][lane >> 1], 0u, 0u, 0u, 0u);
        bar_sync(1, 320);
        const uint32_t tag = *tag_s;
        for (int slice = cta, it = 0; slice < NQS; slice += NS, it++) {
            if (it > 0) {
                bar_sync(2, 256);
                if (tid == 0) {
                    mbar_expect_tx(bar_wq, DM * 48);
                    mbar_expect_tx(bar_wq + 8, DM * 48);
                    for (int i = 0; i < DM / WQ_BOX_ROWS; i++)
                        tma_load_2d(sb + SM_WQ + i * WQ_BOX_ROWS * 96, &tm_wq, slice * 48, i * WQ_BOX_ROWS, bar_wq + 8 * (i >> 1));
                }
            }
            const uint32_t* xn = reinterpret_cast<const uint32_t*>(smem + SM_XN) + 40 * warp + j;
            const uint32_t wa = sb + SM_WQ + (80 * warp + (lane & 7) + 8 * (lane >> 4)) * 96 + ((lane >> 3) & 1) * 16;
            float c[3][4];
#pragma unroll
            for (int t = 0; t < 3; t++) c[t][0] = c[t][1] = c[t][2] = c[t][3] = 0.f;
            mbar_wait(bar_wq + 8 * (warp >> 2), it & 1);
#pragma unroll
            for (int s = 0; s < 5; s++) {
                const uint32_t b0 = xn[8 * s], b1 = xn[8 * s + 4];
#pragma unroll
                for (int t = 0; t < 3; t++) {
                    uint32_t a[4];
                    ldsm4t(a, wa + s * 16 * 96 + t * 32);
                    mma16816(c[t], a[0], a[1], a[2], a[3], b0, b1);
                }
            }
            if (j < 3) {
                qred[warp * 48 + 16 * j + g] = j == 0 ? c[0][0] : j == 1 ? c[1][0] : c[2][0];
                qred[warp * 48 + 16 * j + g + 8] = j == 0 ? c[0][2] : j == 1 ? c[1][2] : c[2][2];
            }
            bar_sync(2, 256);
            if (warp == 0) {
                float2 s = make_float2(0.f, 0.f);
                const int pi = lane < 24 ? lane : 0;
#pragma unroll
                for (int w8 = 0; w8 < 8; w8++) {
                    float2 v = *reinterpret_cast<const float2*>(qred + w8 * 48 + 2 * pi);
                    s.x += v.x;
                    s.y += v.y;
                }
                const uint32_t pk = pack_bf2(s.x, s.y);
                const uint32_t p0 = __shfl_sync(0xffffffffu, pk, 3 * (lane & 7));
                const uint32_t p1 = __shfl_sync(0xffffffffu, pk, 3 * (lane & 7) + 1);
                const uint32_t p2 = __shfl_sync(0xffffffffu, pk, 3 * (lane & 7) + 2);
                if (lane < 8) ll_store(&g_q[slice * 8 + lane], p0, p1, p2, tag);
            }
        }
        bar_sync(2, 256);
        {
            uint32_t* qs = reinterpret_cast<uint32_t*>(smem + SM_Q);
            uint32_t n = 0;
            if (warp == 0) {
                uint4 u;
                while ((u = ll_load(&g_q[lane])).w != tag) {
                    if (++n > SPIN_LIMIT) __trap();
                }
                qs[3 * lane] = u.x;
                qs[3 * lane + 1] = u.y;
                qs[3 * lane + 2] = u.z;
            } else if (warp >= 4) {
                uint4 u[8];
#pragma unroll
                for (int i = 0; i < 8; i++) u[i].w = 0u;
                while (true) {
                    bool ok = true;
#pragma unroll
                    for (int i = 0; i < 8; i++)
                        if (u[i].w != tag) u[i] = ll_load(&g_q[tid - 128 + 128 * i]);
#pragma unroll
                    for (int i = 0; i < 8; i++) ok = ok && (u[i].w == tag);
                    if (ok) break;
                    if (++n > SPIN_LIMIT) __trap();
                    __nanosleep(200);
                }
#pragma unroll
                for (int i = 0; i < 8; i++) {
                    const int un = tid - 128 + 128 * i;
                    if (un >= 32) {
                        qs[3 * un] = u[i].x;
                        qs[3 * un + 1] = u[i].y;
                        qs[3 * un + 2] = u[i].z;
                    }
                }
                __syncwarp();
                if (lane == 0) mbar_arrive(bar_q);
            }
            if (warp < 4) bar_sync(3, 128);
        }

        if (warp < 4) {
            const int mi = lane >> 3, r = lane & 7;
            uint32_t offK[4], offV[4];
            {
                int keyK = 16 * warp + r + 8 * (mi & 1), zK = (mi >> 1) ^ r;
                int keyV = 16 * warp + r + 8 * (mi >> 1), zV = (mi & 1) ^ r;
#pragma unroll
                for (int u = 0; u < 4; u++) {
                    offK[u] = sb + SM_RING + keyK * ROWB + (((2 * u) ^ zK) << 4);
                    offV[u] = sb + SM_RING + keyV * ROWB + (((2 * u) ^ zV) << 4);
                }
            }
            const bool valid = (j == (g >> 1));
            const bool odd = g & 1;
            float acc[12][4];
#pragma unroll
            for (int t = 0; t < 12; t++) acc[t][0] = acc[t][1] = acc[t][2] = acc[t][3] = 0.f;
            float m_run = NEG_INF, r_run = NEG_INF, fr_run = 0.f, l_run = 0.f;
            uint32_t qf[12][2];
            int cur = -1;
            int pub = 0;
            int slot = 0;
            uint32_t ph = 0;
            uint4* pub_p = tid < 64 ? &g_pdat[0][tid >> 4][cta][tid & 15] : &g_phdr[0][cta];
            const int pub_step = tid < 64 ? NCOMB * MAXS * 16 : MAXS;
            const uint32_t a_ow = sb + SM_OBUF + (warp * DH + 16 * j + g) * 4;
            const uint32_t a_or = sb + SM_OBUF + (tid < 64 ? 12 * tid : 0);
            const uint32_t* qs = reinterpret_cast<const uint32_t*>(smem + SM_Q);

            while (true) {
                mbar_wait(bar_full + 8 * slot, ph);
                const int item = meta[slot >> 1];
                const int head = item < 0 ? NH : item / ITEMS_PER_HEAD;
                if (head != cur) {
                    while (pub < head) {
                        const uint32_t par = pub & 1;
                        pub_p = opaque(pub_p);
                        float l = l_run;
                        l += __shfl_xor_sync(0xffffffffu, l, 16);
                        float w0[6], w2[6];
#pragma unroll
                        for (int T = 0; T < 3; T++) {
#pragma unroll
                            for (int b = 0; b < 2; b++) {
                                float v0 = b ? acc[4 * T + 0][1] + acc[4 * T + 0][2] : acc[4 * T + 0][0] + acc[4 * T + 0][3];
                                float v1 = b ? acc[4 * T + 1][1] + acc[4 * T + 1][2] : acc[4 * T + 1][0] + acc[4 * T + 1][3];
                                float v2 = b ? acc[4 * T + 2][1] + acc[4 * T + 2][2] : acc[4 * T + 2][0] + acc[4 * T + 2][3];
                                float v3 = b ? acc[4 * T + 3][1] + acc[4 * T + 3][2] : acc[4 * T + 3][0] + acc[4 * T + 3][3];
                                w0[2 * T + b] = v0 + __shfl_xor_sync(0xffffffffu, v1, 1);
                                w2[2 * T + b] = v2 + __shfl_xor_sync(0xffffffffu, v3, 1);
                            }
                        }
                        l += __shfl_xor_sync(0xffffffffu, l, 8);
#pragma unroll
                        for (int i = 0; i < 6; i++) w0[i] += __shfl_xor_sync(0xffffffffu, w2[i], 2);
                        l += __shfl_xor_sync(0xffffffffu, l, 4);
#pragma unroll
                        for (int i = 0; i < 6; i++) sts32(a_ow + par * (4 * DH * 4) + ((i >> 1) * 64 + (i & 1) * 8) * 4, w0[i]);
                        if (lane < 4) sts32(sb + SM_ML + par * 80 + 16 + warp * 16 + lane * 4, l);
                        if (lane == 0) sts32(sb + SM_ML + par * 80 + warp * 4, r_run);
                        bar_sync(3, 128);
                        if (tid <= 64) {
                            const float4 m4 = lds128(sb + SM_ML + par * 80);
                            float ov[4][3];
                            float4 l4[4];
#pragma unroll
                            for (int w4 = 0; w4 < 4; w4++) {
                                if (tid < 64) {
#pragma unroll
                                    for (int e = 0; e < 3; e++) ov[w4][e] = lds32(a_or + par * (4 * DH * 4) + (w4 * DH + e) * 4);
                                } else {
                                    l4[w4] = lds128(sb + SM_ML + par * 80 + 16 + w4 * 16);
                                    ov[w4][0] = 0.f;
                                    ov[w4][1] = (l4[w4].x + l4[w4].y) + (l4[w4].z + l4[w4].w);
                                    ov[w4][2] = 0.f;
                                }
                            }
                            const float M = fmaxf(fmaxf(m4.x, m4.y), fmaxf(m4.z, m4.w));
                            const float Ms = M == NEG_INF ? 0.f : M;
                            const float f0 = ex2(m4.x - Ms), f1 = ex2(m4.y - Ms), f2 = ex2(m4.z - Ms), f3 = ex2(m4.w - Ms);
                            float r3[3];
#pragma unroll
                            for (int e = 0; e < 3; e++)
                                r3[e] = fmaf(f0, ov[0][e], f1 * ov[1][e]) + fmaf(f2, ov[2][e], f3 * ov[3][e]);
                            ll_store(pub_p, __float_as_uint(tid < 64 ? r3[0] : M), __float_as_uint(r3[1]),
                                     __float_as_uint(r3[2]), tag);
                        }
                        pub_p += pub_step;
#pragma unroll
                        for (int t = 0; t < 12; t++) acc[t][0] = acc[t][1] = acc[t][2] = acc[t][3] = 0.f;
                        m_run = r_run = NEG_INF;
                        l_run = 0.f;
                        pub++;
                    }
                    if (item < 0) break;
                    if (head > 0) mbar_wait(bar_q, 0);
                    cur = head;
                    const uint32_t* qh = qs + head * (DH / 2) + j;
#pragma unroll
                    for (int t = 0; t < 12; t++) {
                        qf[t][0] = qh[((t >> 2) * 8 + ((2 * (t & 3)) ^ g)) * 4];
                        qf[t][1] = qh[((t >> 2) * 8 + ((2 * (t & 3) + 1) ^ g)) * 4];
                    }
                }
                const uint32_t so = slot * CHUNK;
                float s0[4] = {0.f, 0.f, 0.f, 0.f}, s1[4] = {0.f, 0.f, 0.f, 0.f};
#pragma unroll
                for (int t = 0; t < 12; t += 2) {
                    uint32_t a[4], b[4];
                    ldsm4(a, offK[t & 3] + so + (t >> 2) * 128);
                    ldsm4(b, offK[(t + 1) & 3] + so + ((t + 1) >> 2) * 128);
                    mma16816(s0, a[0], a[1], a[2], a[3], qf[t][0], qf[t][1]);
                    mma16816(s1, b[0], b[1], b[2], b[3], qf[t + 1][0], qf[t + 1][1]);
                }
                __syncwarp();
                if (lane == 0) mbar_arrive(bar_empty + 8 * slot);
                float sa = odd ? s0[1] + s1[1] : s0[0] + s1[0];
                float sb2 = odd ? s0[3] + s1[3] : s0[2] + s1[2];
                sa = valid ? bfr(bfr(sa) * QK_SCALE) : NEG_INF;
                sb2 = valid ? bfr(bfr(sb2) * QK_SCALE) : NEG_INF;
                const float mx = warp_max(fmaxf(sa, sb2));
                if (mx > m_run) {
                    const float x2 = mx * LOG2E, r2 = ceilf(x2);
                    const float al = ex2(r_run - r2);
                    r_run = r2;
                    fr_run = r2 - x2;
#pragma unroll
                    for (int t = 0; t < 12; t++) {
                        acc[t][0] *= al;
                        acc[t][1] *= al;
                        acc[t][2] *= al;
                        acc[t][3] *= al;
                    }
                    l_run *= al;
                    m_run = mx;
                }
                const float pa = ex2(fmaf(sa - m_run, LOG2E, -fr_run)), pb = ex2(fmaf(sb2 - m_run, LOG2E, -fr_run));
                uint32_t b0 = 0, b1 = 0;
                if (valid) {
                    const float ha = bfr(pa), hb = bfr(pb);
                    l_run += ha + hb;
                    b0 = odd ? __float_as_uint(ha) : __float_as_uint(ha) >> 16;
                    b1 = odd ? __float_as_uint(hb) : __float_as_uint(hb) >> 16;
                }
                mbar_wait(bar_full + 8 * (slot + 1), ph);
#pragma unroll
                for (int t = 0; t < 12; t++) {
                    uint32_t a[4];
                    ldsm4t(a, offV[t & 3] + so + CHUNK + (t >> 2) * 128);
                    mma16816(acc[t], a[0], a[1], a[2], a[3], b0, b1);
                }
                __syncwarp();
                if (lane == 0) mbar_arrive(bar_empty + 8 * (slot + 1));
                slot += 2;
                if (slot == NSLOT) { slot = 0; ph ^= 1; }
            }
        }
        {
            bar_sync(2, 256);
            uint32_t wgf[5][4], wuf[5][4], wdf[6][4];
            const bool gu = cta < NGU;
            auto ucol = [](int U, int e) { return U < 16 ? 8 * (4 * (U >> 3) + e) + (U & 7) : 8 * (8 + (e & 1)) + 2 * (U - 16) + (e >> 1); };
            const int mi = lane >> 3, r = lane & 7;
            const int U = lane < 20 ? lane : 0;
            const uint4* attn_p = opaque(&g_attn[0][warp][U]);
            uint4* act_st = opaque(&g_act[gu ? cta : 0][(lane >> 1) & 3]);
            const uint4* act_p0 = opaque(&g_act[12 * warp + g][j]);
            const uint4* act_p1 = opaque(&g_act[12 * warp + 8 + (g & 3)][j]);
            __nv_bfloat16* out_p = opaque(p.out + (dn_idx >= 0 ? dn_idx * 8 : 0) + (lane & 7));
            const unsigned int* bell_p = opaque(&g_bell[(cta * 8 + warp) & 31][j]);
            const uint32_t a_h = opaque(sb + SM_H + (80 * warp + ucol(U, 0)) * 4);
            const uint32_t a_h2 = opaque(a_h + (U < 16 ? 64 : 4));
            const uint32_t a_st = opaque(sb + SM_ST + warp * 16);
            const uint32_t a_red = opaque(sb + SM_RED + warp * 256 + (g + 8 * j) * 8);
            const uint32_t a_fin = opaque(sb + SM_RED + (lane & 7) * 16);
            const uint32_t a_r2 = opaque(sb + SM_RED2 + g * 32 + warp * 4);
            const uint32_t a_f2 = opaque(sb + SM_RED2 + (lane & 7) * 32);
            const uint32_t a_ho = opaque(sb + SM_H + ((dn_idx >= 0 ? dn_idx * 8 : 0) + (lane & 7)) * 4);
            const uint32_t tag4 = tag & 15u;
            if (gu || warp == dn_idx / 10) {
                float xr[4];
#pragma unroll
                for (int e = 0; e < 4; e++) xr[e] = __bfloat162float(p.x[80 * warp + ucol(U, e)]);
                uint32_t n = 0;
                if (gu) {
                    mbar_wait(bar_w, 0);
#pragma unroll
                    for (int s = 0; s < 5; s++) {
                        const int row = 80 * warp + ucol(4 * s + (r >> 1), 2 * (mi >> 1) + (r & 1));
                        ldsm4t(wgf[s], sb + SM_WG + row * 32 + (mi & 1) * 16);
                        ldsm4t(wuf[s], sb + SM_WU + row * 32 + (mi & 1) * 16);
                    }
                }
                while (!__all_sync(0xffffffffu, ld_relaxed(bell_p) == tag)) {
                    if (++n > SPIN_LIMIT) __trap();
                }
                float a0, a1, a2, a3;
                while (true) {
                    uint4 u[4];
#pragma unroll
                    for (int q = 0; q < 4; q++) u[q] = ll_load(attn_p + q * 256);
                    const uint32_t bad = (u[0].w ^ tag4) | (u[1].w ^ tag4) | (u[2].w ^ tag4) | (u[3].w ^ tag4);
                    a0 = (__uint_as_float(u[0].x) + __uint_as_float(u[1].x)) + (__uint_as_float(u[2].x) + __uint_as_float(u[3].x));
                    a1 = (__uint_as_float(u[0].y) + __uint_as_float(u[1].y)) + (__uint_as_float(u[2].y) + __uint_as_float(u[3].y));
                    a2 = (__uint_as_float(u[0].z) + __uint_as_float(u[1].z)) + (__uint_as_float(u[2].z) + __uint_as_float(u[3].z));
                    a3 = (__uint_as_float(u[0].w ^ tag4) + __uint_as_float(u[1].w ^ tag4)) +
                         (__uint_as_float(u[2].w ^ tag4) + __uint_as_float(u[3].w ^ tag4));
                    if (__all_sync(0xffffffffu, (bad & 15u) == 0)) break;
                    if (++n > SPIN_LIMIT) __trap();
                }
                const uint32_t hb0 = pack_bf2(xr[0] + bfr(a0), xr[1] + bfr(a1));
                const uint32_t hb1 = pack_bf2(xr[2] + bfr(a2), xr[3] + bfr(a3));
                const float h0 = bf_lo(hb0), h1 = bf_hi(hb0), h2 = bf_lo(hb1), h3 = bf_hi(hb1);
                if (lane < 20) {
                    sts32(a_h, h0);
                    sts32(a_h + 32, h1);
                    sts32(a_h2, h2);
                    sts32(a_h2 + 32, h3);
                }
                if (gu) {
                    uint32_t f0[5], f1[5];
                    const uint32_t t0 = lane < 20 ? hb0 : 0x3f803f80u, t1 = lane < 20 ? hb1 : 0x3f803f80u;
                    const float piv = __shfl_sync(0xffffffffu, h0, 0);
#pragma unroll
                    for (int s = 0; s < 5; s++) {
                        f0[s] = __shfl_sync(0xffffffffu, t0, g < 4 ? 4 * s + j : 31);
                        f1[s] = __shfl_sync(0xffffffffu, t1, g < 4 ? 4 * s + j : 31);
                    }
                    const float d0 = h0 - piv, d1 = h1 - piv, d2 = h2 - piv, d3 = h3 - piv;
                    float s1 = lane < 20 ? (d0 + d1) + (d2 + d3) : 0.f;
                    float s2 = lane < 20 ? fmaf(d0, d0, d1 * d1) + fmaf(d2, d2, d3 * d3) : 0.f;
                    float cg[2][4], cu[2][4];
#pragma unroll
                    for (int i = 0; i < 2; i++) {
                        cg[i][0] = cg[i][1] = cg[i][2] = cg[i][3] = 0.f;
                        cu[i][0] = cu[i][1] = cu[i][2] = cu[i][3] = 0.f;
                    }
#pragma unroll
                    for (int s = 0; s < 5; s++) {
                        const float t1 = __shfl_xor_sync(0xffffffffu, s1, 16 >> s);
                        const float t2 = __shfl_xor_sync(0xffffffffu, s2, 16 >> s);
                        mma16816(cg[s & 1], wgf[s][0], wgf[s][1], wgf[s][2], wgf[s][3], f0[s], f1[s]);
                        mma16816(cu[s & 1], wuf[s][0], wuf[s][1], wuf[s][2], wuf[s][3], f0[s], f1[s]);
                        s1 += t1;
                        s2 += t2;
                    }
                    const bool o1 = j & 1;
                    const float ga = o1 ? cg[0][2] + cg[1][2] : cg[0][0] + cg[1][0];
                    const float ua = o1 ? cu[0][2] + cu[1][2] : cu[0][0] + cu[1][0];
                    sts64(a_red, ga, ua);
                    if (lane == 0) sts128(a_st, fmaf(80.f, piv, s1), piv, 2.f * s1, s2);
                }
            }
            bar_sync(2, 256);
            if (gu && warp == 4) {
                float4 st[8], ra[8], rc[8];
#pragma unroll
                for (int w8 = 0; w8 < 8; w8++) st[w8] = lds128(sb + SM_ST + w8 * 16);
#pragma unroll
                for (int w8 = 0; w8 < 8; w8++) {
                    ra[w8] = lds128(a_fin + w8 * 256);
                    rc[w8] = lds128(a_fin + w8 * 256 + 128);
                }
#define SUM8(arr, f) (((arr[0].f + arr[1].f) + (arr[2].f + arr[3].f)) + ((arr[4].f + arr[5].f) + (arr[6].f + arr[7].f)))
                const float mean = SUM8(st, x) * (1.0f / DM);
#pragma unroll
                for (int w8 = 0; w8 < 8; w8++) {
                    const float dl = st[w8].y - mean;
                    st[w8].w = fmaf(dl, fmaf(80.f, dl, st[w8].z), st[w8].w);
                }
                const float var = fmaxf(SUM8(st, w) * (1.0f / DM), 0.f);
                const float rs = rcp_fast(bfr(sqrt_fast(bfr(bfr(var) + 1e-5f))));
                const float mean_b = bfr(mean);
                const float g0 = bfr(fmaf(-mean_b, SUM8(rc, x), SUM8(ra, x)) * rs), u0 = bfr(fmaf(-mean_b, SUM8(rc, y), SUM8(ra, y)) * rs);
                const float g1 = bfr(fmaf(-mean_b, SUM8(rc, z), SUM8(ra, z)) * rs), u1 = bfr(fmaf(-mean_b, SUM8(rc, w), SUM8(ra, w)) * rs);
#undef SUM8
                const float act0 = bfr(g0 * rcp_fast(1.0f + ex2(-LOG2E * g0))) * u0;
                const float act1 = bfr(g1 * rcp_fast(1.0f + ex2(-LOG2E * g1))) * u1;
                const uint32_t pk = pack_bf2(act0, act1);
                const uint32_t pn = __shfl_down_sync(0xffffffffu, pk, 1);
                if (lane < 8 && !(lane & 1)) ll_store(act_st, pk, pn, 0u, tag);
            }
            if (dn_idx >= 0) {
                const float hres = lds32(a_ho);
                mbar_wait(bar_w + 8, 0);
                {
                    const uint32_t wa = sb + SM_WD + (192 * warp + 16 * (mi & 1) + 4 * (r >> 1) + 2 * (mi >> 1) + (r & 1)) * 16;
#pragma unroll
                    for (int s = 0; s < 6; s++) ldsm4t(wdf[s], wa + s * 512);
                }
                uint2 u0, u1;
                uint32_t n = 0;
                while (true) {
                    const uint4 a0 = ll_load(act_p0), a1 = ll_load(act_p1);
                    u0 = make_uint2(a0.x, a0.y);
                    u1 = make_uint2(a1.x, a1.y);
                    if (__all_sync(0xffffffffu, a0.w == tag && a1.w == tag)) break;
                    if (++n > SPIN_LIMIT) __trap();
                }
                float c[3][4];
#pragma unroll
                for (int i = 0; i < 3; i++) c[i][0] = c[i][1] = c[i][2] = c[i][3] = 0.f;
#pragma unroll
                for (int i = 0; i < 6; i++) {
                    const bool on = (g >> 1) == (i < 4 ? i : i - 4);
                    const uint32_t e0 = on ? (i < 4 ? u0.x : u1.x) : 0u, e1 = on ? (i < 4 ? u0.y : u1.y) : 0u;
                    mma16816(c[i % 3], wdf[i][0], wdf[i][1], wdf[i][2], wdf[i][3], e0, e1);
                }
                float e0 = ((c[0][0] + c[0][3]) + (c[1][0] + c[1][3])) + (c[2][0] + c[2][3]);
                e0 += __shfl_xor_sync(0xffffffffu, e0, 1);
                e0 += __shfl_xor_sync(0xffffffffu, e0, 2);
                if (j == 0) sts32(a_r2, e0);
                bar_sync(2, 256);
                if (warp == 4 && lane < 8) {
                    const float4 ra = lds128(a_f2), rb = lds128(a_f2 + 16);
                    const float sum = ((ra.x + ra.y) + (ra.z + ra.w)) + ((rb.x + rb.y) + (rb.z + rb.w));
                    const uint32_t res = pack_bf2(hres + bfr(sum), 0.f);
                    asm volatile("st.global.u16 [%0], %1;" ::"l"(out_p), "h"((unsigned short)res) : "memory");
                    if (lane == 0 && cta == NS - 1) *(volatile unsigned int*)&g_epoch = tag;
                }
            }
        }
    } else {
        const int qd = cta - NS;
        if (warp == 8) {
            if (lane == 0) {
                for (int s = 0; s < NWO; s++) {
                    mbar_init(bar_full + 8 * s, 1);
                    mbar_init(bar_empty + 8 * s, 8);
                }
                asm volatile("fence.mbarrier_init.release.cluster;" ::: "memory");
            }
            __syncwarp();
            asm volatile("bar.arrive 1, 288;" ::: "memory");
            uint64_t pol;
            asm volatile("createpolicy.fractional.L2::evict_first.b64 %0, 1.0;" : "=l"(pol));
            int slot = 0;
            uint32_t ph = 0;
            for (int h = 0; h < NH; h++) {
                if (lane == 0) {
                    if (h >= NWO) mbar_wait(bar_empty + 8 * slot, ph ^ 1);
                    mbar_expect_tx(bar_full + 8 * slot, 48 * DM * 2);
                }
                __syncwarp();
                const __nv_bfloat16* src = p.wo + (size_t)(h * DH + qd * 48) * DM;
                bulk_load(sb + slot * WO_BUF + lane * WO_PITCH, src + lane * DM, DM * 2, bar_full + 8 * slot, pol);
                if (lane < 16)
                    bulk_load(sb + slot * WO_BUF + (32 + lane) * WO_PITCH, src + (32 + lane) * DM, DM * 2,
                              bar_full + 8 * slot, pol);
                if (++slot == NWO) { slot = 0; ph ^= 1; }
            }
            return;
        }
        if (warp == 9) return;
        if (tid == 255) *tag_s = *(volatile unsigned int*)&g_epoch + 1;
        bar_sync(1, 288);
        const uint32_t tag = *tag_s;
        float acc[5][4];
#pragma unroll
        for (int t = 0; t < 5; t++) acc[t][0] = acc[t][1] = acc[t][2] = acc[t][3] = 0.f;
        const uint32_t a_ow = opaque(sb + SC_OB + warp * 192 + (lane & 15) * 12);
        const uint32_t a_or = opaque(sb + SC_OB + (lane < 24 ? lane : 0) * 8);
        uint4* attn_st = opaque(&g_attn[qd][warp][j == 0 ? g : j == 1 ? 8 + g : 16 + (g >> 1)]);
        const int mi = lane >> 3, r = lane & 7;
        const uint32_t woff = sb + (r + 8 * (mi >> 1)) * WO_PITCH + (80 * warp + 8 * (mi & 1)) * 2;
        const int dc = 2 * warp + (lane >> 4);
        int slot = 0;
        uint32_t ph = 0;
        const uint4* hp0 = &g_phdr[0][lane];
        const uint4* dp0 = &g_pdat[0][qd][dc][lane & 15];
        unsigned int* bell_st = opaque(&g_bell[lane][qd]);
        if (warp == 0) st_relaxed(bell_st, 0u);
        for (int h = 0; h < NH; h++) {
            const uint4* hp = opaque(hp0 + h * MAXS);
            const uint4* dp = opaque(dp0 + h * (NCOMB * MAXS * 16));
            uint32_t wf[5][3][4];
            mbar_wait(bar_full + 8 * slot, ph);
#pragma unroll
            for (int t = 0; t < 5; t++)
#pragma unroll
                for (int s = 0; s < 3; s++) ldsm4t(wf[t][s], woff + slot * WO_BUF + s * 16 * WO_PITCH + t * 32);
            __syncwarp();
            if (lane == 0) mbar_arrive(bar_empty + 8 * slot);
            if (++slot == NWO) { slot = 0; ph ^= 1; }

            uint4 hd[4], u[8];
#pragma unroll
            for (int i = 0; i < 4; i++) hd[i] = make_uint4(__float_as_uint(NEG_INF), 0u, 0u, lane + 32 * i < NS ? ~tag : tag);
#pragma unroll
            for (int i = 0; i < 8; i++) u[i] = make_uint4(0u, 0u, 0u, dc + 16 * i < NS ? ~tag : tag);
            uint32_t n = 0;
            if (h < NH - 1) {
                while (true) {
                    bool ok = true;
#pragma unroll
                    for (int i = 0; i < 4; i++)
                        if (hd[i].w != tag) hd[i] = ll_load(hp + 32 * i);
#pragma unroll
                    for (int i = 0; i < 4; i++) ok = ok && (hd[i].w == tag);
                    if (__all_sync(0xffffffffu, ok)) break;
                    if (++n > SPIN_LIMIT) __trap();
                    __nanosleep(1000);
                }
            }
            while (true) {
                bool ok = true;
#pragma unroll
                for (int i = 0; i < 4; i++)
                    if (hd[i].w != tag) hd[i] = ll_load(hp + 32 * i);
#pragma unroll
                for (int i = 0; i < 8; i++)
                    if (u[i].w != tag) u[i] = ll_load(dp + 256 * i);
#pragma unroll
                for (int i = 0; i < 4; i++) ok = ok && (hd[i].w == tag);
#pragma unroll
                for (int i = 0; i < 8; i++) ok = ok && (u[i].w == tag);
                if (__all_sync(0xffffffffu, ok)) break;
                if (++n > SPIN_LIMIT) __trap();
            }
            if (h == NH - 1 && warp == 0) st_relaxed(bell_st, tag);
            const float M = warp_max(fmaxf(fmaxf(__uint_as_float(hd[0].x), __uint_as_float(hd[1].x)),
                                           fmaxf(__uint_as_float(hd[2].x), __uint_as_float(hd[3].x))));
            float f[4];
#pragma unroll
            for (int i = 0; i < 4; i++) f[i] = ex2(__uint_as_float(hd[i].x) - M);
            float L = fmaf(f[0], __uint_as_float(hd[0].y), f[1] * __uint_as_float(hd[1].y)) +
                      fmaf(f[2], __uint_as_float(hd[2].y), f[3] * __uint_as_float(hd[3].y));
            float fa[4], fb[4];
#pragma unroll
            for (int i = 0; i < 4; i++) {
                fa[i] = __shfl_sync(0xffffffffu, f[i], dc);
                fb[i] = __shfl_sync(0xffffffffu, f[i], dc + 16);
            }
            L += __shfl_xor_sync(0xffffffffu, L, 16);
            float o0 = 0.f, o1 = 0.f, o2 = 0.f, o3 = 0.f, o4 = 0.f, o5 = 0.f;
#pragma unroll
            for (int i = 0; i < 4; i++) {
                o0 = fmaf(fa[i], __uint_as_float(u[2 * i].x), o0);
                o1 = fmaf(fa[i], __uint_as_float(u[2 * i].y), o1);
                o2 = fmaf(fa[i], __uint_as_float(u[2 * i].z), o2);
                o3 = fmaf(fb[i], __uint_as_float(u[2 * i + 1].x), o3);
                o4 = fmaf(fb[i], __uint_as_float(u[2 * i + 1].y), o4);
                o5 = fmaf(fb[i], __uint_as_float(u[2 * i + 1].z), o5);
            }
            L += __shfl_xor_sync(0xffffffffu, L, 8);
            o0 += o3;
            o1 += o4;
            o2 += o5;
            o0 += __shfl_xor_sync(0xffffffffu, o0, 16);
            o1 += __shfl_xor_sync(0xffffffffu, o1, 16);
            o2 += __shfl_xor_sync(0xffffffffu, o2, 16);
            L += __shfl_xor_sync(0xffffffffu, L, 4);
            const uint32_t par = (h & 1) * (8 * 192);
            if (lane < 16) {
                sts32(a_ow + par, o0);
                sts32(a_ow + par + 4, o1);
                sts32(a_ow + par + 8, o2);
            }
            bar_sync(2, 256);
            L += __shfl_xor_sync(0xffffffffu, L, 2);
            L += __shfl_xor_sync(0xffffffffu, L, 1);
            const float rL = rcp_fast(L);
            float2 ov[8];
#pragma unroll
            for (int w8 = 0; w8 < 8; w8++) ov[w8] = lds64(a_or + par + w8 * 192);
            const float e0 = ((ov[0].x + ov[1].x) + (ov[2].x + ov[3].x)) + ((ov[4].x + ov[5].x) + (ov[6].x + ov[7].x));
            const float e1 = ((ov[0].y + ov[1].y) + (ov[2].y + ov[3].y)) + ((ov[4].y + ov[5].y) + (ov[6].y + ov[7].y));
            const uint32_t pk = pack_bf2(e0 * rL, e1 * rL);
            uint32_t b0[3], b1[3];
#pragma unroll
            for (int s = 0; s < 3; s++) {
                b0[s] = __shfl_sync(0xffffffffu, pk, 8 * s + j);
                b1[s] = __shfl_sync(0xffffffffu, pk, 8 * s + 4 + j);
            }
#pragma unroll
            for (int s = 0; s < 3; s++)
#pragma unroll
                for (int t = 4; t >= 0; t--)
                    mma16816(acc[t], wf[t][s][0], wf[t][s][1], wf[t][s][2], wf[t][s][3], b0[s], b1[s]);
            const float n8 = __shfl_down_sync(0xffffffffu, acc[4][0], 4), n9 = __shfl_down_sync(0xffffffffu, acc[4][2], 4);
            const float v0 = j == 0 ? acc[0][0] : j == 1 ? acc[2][0] : acc[4][0];
            const float v1 = j == 0 ? acc[0][2] : j == 1 ? acc[2][2] : acc[4][2];
            const float v2 = j == 0 ? acc[1][0] : j == 1 ? acc[3][0] : n8;
            const float v3 = j == 0 ? acc[1][2] : j == 1 ? acc[3][2] : n9;
            if (j < 2 || (j == 2 && !(g & 1)))
                ll_store(attn_st, __float_as_uint(v0), __float_as_uint(v1), __float_as_uint(v2),
                         (__float_as_uint(v3) & ~15u) | ((tag & 15u) ^ (h == NH - 1 ? 0u : 8u)));
        }
    }
}

}

extern "C" void kernel_launch(void* const* d_in, const int* in_sizes, int n_in, void* d_out, int out_size) {
    using namespace fused;
    static int grid = 0;
    static CUtensorMap tm[4];
    static const void* tm_ptr[4] = {nullptr, nullptr, nullptr, nullptr};
    if (grid == 0) {
        int dev = 0, sms = 0;
        cudaGetDevice(&dev);
        cudaDeviceGetAttribute(&sms, cudaDevAttrMultiProcessorCount, dev);
        cudaFuncSetAttribute(fused_kernel, cudaFuncAttributeMaxDynamicSharedMemorySize, SM_TOTAL);
        grid = sms < MAXS + NCOMB ? sms : MAXS + NCOMB;
    }
    {
        const int idx[4] = {3, 6, 7, 8};
        const cuuint64_t cols[4] = {HD, FF, FF, DM}, rows[4] = {DM, DM, DM, FF};
        const cuuint32_t bc[4] = {48, 16, 16, 8}, br[4] = {WQ_BOX_ROWS, 160, 160, 256};
        for (int i = 0; i < 4; i++) {
            if (tm_ptr[i] == d_in[idx[i]]) continue;
            typedef CUresult (*EncodeFn)(CUtensorMap*, CUtensorMapDataType, cuuint32_t, void*, const cuuint64_t*,
                                         const cuuint64_t*, const cuuint32_t*, const cuuint32_t*, CUtensorMapInterleave,
                                         CUtensorMapSwizzle, CUtensorMapL2promotion, CUtensorMapFloatOOBfill);
            void* fn = nullptr;
            cudaDriverEntryPointQueryResult qr;
            cudaGetDriverEntryPoint("cuTensorMapEncodeTiled", &fn, cudaEnableDefault, &qr);
            cuuint64_t gdim[2] = {cols[i], rows[i]};
            cuuint64_t gstr[1] = {cols[i] * 2};
            cuuint32_t box[2] = {bc[i], br[i]};
            cuuint32_t estr[2] = {1, 1};
            ((EncodeFn)fn)(&tm[i], CU_TENSOR_MAP_DATA_TYPE_BFLOAT16, 2, d_in[idx[i]], gdim, gstr, box, estr,
                           CU_TENSOR_MAP_INTERLEAVE_NONE, CU_TENSOR_MAP_SWIZZLE_NONE,
                           CU_TENSOR_MAP_L2_PROMOTION_L2_128B, CU_TENSOR_MAP_FLOAT_OOB_FILL_NONE);
            tm_ptr[i] = d_in[idx[i]];
        }
    }
    Params p;
    p.x = (const __nv_bfloat16*)d_in[0];
    p.k = (const char*)d_in[1];
    p.v = (const char*)d_in[2];
    p.wo = (const __nv_bfloat16*)d_in[4];
    p.out = (__nv_bfloat16*)d_out;
    fused_kernel<<<grid, NTHREADS, SM_TOTAL, cudaStreamPerThread>>>(p, tm[0], tm[1], tm[2], tm[3]);
}
```
